```python
import torch

def _softmax(x, axis=-1):
    return torch.softmax(x, dim=axis)
def _gelu(x):
    return torch.nn.functional.gelu(x, approximate="tanh")
def _silu(x):
    return torch.nn.functional.silu(x)
def _sigmoid(x):
    return torch.sigmoid(x)
def _layernorm(x, axis=-1, eps=1e-5):
    m = x.mean(dim=axis, keepdim=True)
    v = x.var(dim=axis, keepdim=True, unbiased=False)
    return (x - m) / torch.sqrt(v + eps)
def _scatter_add(tgt, idx, src, axis=0):
    return tgt.clone().index_add_(axis, idx, src)
def _segment_sum(src, seg, n):
    out = torch.zeros((n,) + src.shape[1:], dtype=src.dtype)
    return out.index_add_(0, seg, src)
def _pad(x, pw):
    flat = tuple(v for pair in reversed(pw) for v in pair)
    return torch.nn.functional.pad(x, flat)

kernel_name = 'interleave_layers__gqa_block_cached__glu_gated_reglu__decode'

def setup_inputs():

    _w = (lambda a: (lambda t: t.to(torch.bfloat16) if t.is_floating_point() else t)(torch.as_tensor(a)))
    def _A_setup():
        B, Sq, D = 1, 1, 512
        Hq, Hkv, Sk, Dh = 32, 8, 65536, 128
        assert Hq % Hkv == 0, (Hq, Hkv)
        return {
            "x": _w((lambda *s: torch.randn(*s, dtype=torch.bfloat16) * 0.05)(B, Sq, D)),
            "k_cache": _w((lambda *s: torch.randn(*s, dtype=torch.bfloat16) * 0.8)(B, Hkv, Sk, Dh)),
            "v_cache": _w((lambda *s: torch.randn(*s, dtype=torch.bfloat16) * 1.6)(B, Hkv, Sk, Dh)),
            "wq": _w((lambda *s: torch.randn(*s, dtype=torch.bfloat16) * 0.8)(D, Hq * Dh) * (D ** -0.5)),
            "wo": _w((lambda *s: torch.randn(*s, dtype=torch.bfloat16) * 1.6)(Hq * Dh, D) * ((Hq * Dh) ** -0.5)),
        }
    _A_in = _A_setup()

    def _B_setup():
        B, S, D, F = 1, 1, 512, 1792
        return {
            "x": _w((lambda *s: torch.randn(*s, dtype=torch.bfloat16) * 0.05)(B, S, D)),
            "W_gate": _w((lambda *s: torch.randn(*s, dtype=torch.bfloat16) * 0.2)(D, F) * (2.0 / D) ** 0.5),
            "W_up": _w((lambda *s: torch.randn(*s, dtype=torch.bfloat16) * 0.2)(D, F) * (2.0 / D) ** 0.5),
            "W_down": _w((lambda *s: torch.randn(*s, dtype=torch.bfloat16) * 0.2)(F, D) * (1.0 / F) ** 0.5),
        }
    _B_in = _B_setup()

    return {
        "A_x": _A_in["x"],
        "A_k_cache": _A_in["k_cache"],
        "A_v_cache": _A_in["v_cache"],
        "A_wq": _A_in["wq"],
        "A_wo": _A_in["wo"],
        "B_x": _B_in["x"],
        "B_W_gate": _B_in["W_gate"],
        "B_W_up": _B_in["W_up"],
        "B_W_down": _B_in["W_down"],
    }

def reference(A_x, A_k_cache, A_v_cache, A_wq, A_wo, B_x, B_W_gate, B_W_up, B_W_down):
    def _A_ref(x, k_cache, v_cache, wq, wo):
        B, Sq, D = x.shape
        Hq, Dh = 32, 128
        Hkv = k_cache.shape[1]
        rep = Hq // Hkv
        q = (lambda x, *d: x.permute(*d))((x @ wq).reshape(B, Sq, Hq, Dh), 0, 2, 1, 3)
        k = (lambda x, n, axis: torch.repeat_interleave(x, n, dim=axis))(k_cache, rep, axis=1)
        v = (lambda x, n, axis: torch.repeat_interleave(x, n, dim=axis))(v_cache, rep, axis=1)
        scores = torch.einsum("bhqd,bhkd->bhqk", q, k) * (Dh ** -0.5)
        p = _softmax(scores, axis=-1)
        o = torch.einsum("bhqk,bhkd->bhqd", p, v)
        return (lambda x, *d: x.permute(*d))(o, 0, 2, 1, 3).reshape(B, Sq, Hq * Dh) @ wo

    def _B_ref(x, W_gate, W_up, W_down):
        gate = torch.einsum("bsd,df->bsf", x, W_gate)
        up = torch.einsum("bsd,df->bsf", x, W_up)
        gate = gate * (lambda x, dt: x.to(dt))(gate > 0, gate.dtype)
        h = gate * up
        return torch.einsum("bsf,fd->bsd", h, W_down)

    x = A_x
    x = x + _A_ref(_layernorm(x, axis=-1), A_k_cache, A_v_cache, A_wq, A_wo)
    x = x + _B_ref(_layernorm(x, axis=-1), B_W_gate, B_W_up, B_W_down)
    x = x + _A_ref(_layernorm(x, axis=-1), A_k_cache, A_v_cache, A_wq, A_wo)
    x = x + _B_ref(_layernorm(x, axis=-1), B_W_gate, B_W_up, B_W_down)
    return x
```

```cpp
#include <cuda_runtime.h>
#include <cuda_bf16.h>
#include <cuda.h>
#include <stdint.h>

namespace {

constexpr int NCTA      = 132;
constexpr int NUNIT     = 33;
constexpr int NTILE     = 1024;
constexpr int SLOT      = 16384;
constexpr int T_X       = 5 * NUNIT;
constexpr int T_DYN0    = T_X + 16;
#define NKEEP 205
#define KEEP_TAILSKIP 40
#define KRATIO 1
#define NKFIRST 2
#define JIT_WIN 40
#define D_H1 0
#define D_RS 700
#define D_AG 250
#define D_SKIP 2000
#define GU_FIRST 2
#define WQ_FIRST 1
#define WPF 40
#define WO_EARLY 12
#define TAIL_EARLY 0
#define PD 2
#define QAT 1
#define PF_REM 150
#define PART_EF 2
#define PF_T0 0
#define MID_NPRE 1
#define S1_NPRE 1
#define VPRE 2
#define DBG_U 0
#define DBG_PH 0
constexpr int T_KEEP0   = NTILE - NKEEP;
constexpr int T_KEEPEND = NTILE - KEEP_TAILSKIP;
constexpr int KEEPCAP   = 30;
constexpr int XREP      = 4;
constexpr unsigned SPIN_LIMIT = 1u << 22;

constexpr uint32_t SM_BASE  = 1024;
constexpr uint32_t SM_SLOTS = SM_BASE;
constexpr uint32_t SM_Q     = SM_SLOTS + 14 * SLOT;
constexpr uint32_t SM_P     = SM_Q + 1024;
constexpr uint32_t SM_RED   = SM_P + 1024;
constexpr uint32_t SM_BAR   = SM_RED + 512;
constexpr uint32_t SM_WBAR  = SM_BAR + 112;
constexpr uint32_t SM_TBAR  = SM_BAR + 120;
constexpr uint32_t SM_MX    = SM_BAR + 128;
constexpr uint32_t SM_KEEP  = SM_MX + 128;
constexpr uint32_t SM_ST    = SM_KEEP + 128;
constexpr uint32_t SM_XR    = SM_ST + 32;
constexpr int SM_TOTAL      = SM_XR + 16 - SM_BASE;
static_assert(SM_TOTAL <= 232448, "smem");

struct Scratch {
    uint4 part[128][8][NUNIT][2];
    uint4 r[128][128][2];
    uint4 x1[XREP][128][2];
    uint4 x2[XREP][128][2];
    uint4 q[2][2][8][128];
    unsigned ticket[2][8][32];
    unsigned done[32];
    unsigned epoch;
};
__device__ Scratch g_scratch;
#define g_s (*p.s)
#define TS(i)
#define TSW(i)
#define TT(ph, head, tile)

struct Maps { CUtensorMap k, v, wq, wo, wg, wu, wd; };
struct Params {
    const __nv_bfloat16* x;
    const char* k;
    const char* v;
    const char* wq;
    const char* wo;
    const char* wg;
    const char* wu;
    const char* wd;
    __nv_bfloat16* out;
    Scratch* s;
};

__device__ __forceinline__ void mbar_init(uint32_t bar, uint32_t cnt) {
    asm volatile("mbarrier.init.shared::cta.b64 [%0], %1;" ::"r"(bar), "r"(cnt) : "memory");
}
__device__ __forceinline__ void mbar_wait(uint32_t bar, uint32_t parity) {
    uint32_t ok, it = 0;
    do {
        asm volatile("{\n.reg .pred p;\nmbarrier.try_wait.parity.shared::cta.b64 p, [%1], %2;\nselp.u32 %0, 1, 0, p;\n}"
                     : "=r"(ok) : "r"(bar), "r"(parity) : "memory");
        if (++it > SPIN_LIMIT) __trap();
    } while (!ok);
}
__device__ __forceinline__ uint64_t pol_first() {
    uint64_t p; asm volatile("createpolicy.fractional.L2::evict_first.b64 %0, 1.0;" : "=l"(p)); return p;
}
__device__ __forceinline__ uint64_t pol_normal() {
    uint64_t p; asm volatile("createpolicy.fractional.L2::evict_normal.b64 %0, 1.0;" : "=l"(p)); return p;
}
__device__ __forceinline__ void tma_rows(const CUtensorMap* tm, int row, uint32_t dst, uint32_t bar) {
    asm volatile("mbarrier.arrive.expect_tx.shared::cta.b64 _, [%0], %1;" ::"r"(bar), "r"(SLOT) : "memory");
    asm volatile("cp.async.bulk.tensor.3d.shared::cluster.global.mbarrier::complete_tx::bytes.L2::cache_hint "
                 "[%0], [%1, {%2, %3, %4}], [%5], %6;"
                 ::"r"(dst), "l"(tm), "r"(0), "r"(row), "r"(0), "r"(bar), "l"(pol_first()) : "memory");
}
__device__ __forceinline__ void tma_tile(const CUtensorMap* tm, int gtile, uint32_t dst, uint32_t bar) {
    tma_rows(tm, gtile * 64, dst, bar);
}
__device__ __forceinline__ void expect_tx(uint32_t bar, uint32_t bytes) {
    asm volatile("mbarrier.arrive.expect_tx.shared::cta.b64 _, [%0], %1;" ::"r"(bar), "r"(bytes) : "memory");
}
__device__ __forceinline__ void tma_2d(const CUtensorMap* tm, int c0, int c1, uint32_t dst, uint32_t bar) {
    asm volatile("cp.async.bulk.tensor.2d.shared::cluster.global.mbarrier::complete_tx::bytes.L2::cache_hint "
                 "[%0], [%1, {%2, %3}], [%4], %5;"
                 ::"r"(dst), "l"(tm), "r"(c0), "r"(c1), "r"(bar), "l"(pol_first()) : "memory");
}
__device__ __forceinline__ void l2_prefetch(const void* p, uint32_t bytes, uint64_t pol) {
    asm volatile("cp.async.bulk.prefetch.L2.global.L2::cache_hint [%0], %1, %2;" ::"l"(p), "r"(bytes), "l"(pol) : "memory");
}
__device__ __forceinline__ void ldsm4(uint32_t* r, uint32_t a) {
    asm volatile("ldmatrix.sync.aligned.m8n8.x4.shared.b16 {%0,%1,%2,%3}, [%4];"
                 : "=r"(r[0]), "=r"(r[1]), "=r"(r[2]), "=r"(r[3]) : "r"(a) : "memory");
}
__device__ __forceinline__ void ldsm4t(uint32_t* r, uint32_t a) {
    asm volatile("ldmatrix.sync.aligned.m8n8.x4.trans.shared.b16 {%0,%1,%2,%3}, [%4];"
                 : "=r"(r[0]), "=r"(r[1]), "=r"(r[2]), "=r"(r[3]) : "r"(a) : "memory");
}
__device__ __forceinline__ void mma(float* c, const uint32_t* a, uint32_t b0, uint32_t b1) {
    asm volatile("mma.sync.aligned.m16n8k16.row.col.f32.bf16.bf16.f32 {%0,%1,%2,%3}, {%4,%5,%6,%7}, {%8,%9}, {%0,%1,%2,%3};"
                 : "+f"(c[0]), "+f"(c[1]), "+f"(c[2]), "+f"(c[3])
                 : "r"(a[0]), "r"(a[1]), "r"(a[2]), "r"(a[3]), "r"(b0), "r"(b1));
}
__device__ __forceinline__ uint32_t movm(uint32_t a) {
    uint32_t d; asm volatile("movmatrix.sync.aligned.m8n8.trans.b16 %0, %1;" : "=r"(d) : "r"(a)); return d;
}
__device__ __forceinline__ uint32_t pack_bf16(float lo, float hi) {
    uint32_t d; asm("cvt.rn.bf16x2.f32 %0, %1, %2;" : "=r"(d) : "f"(hi), "f"(lo)); return d;
}
__device__ __forceinline__ float bf16r(float v) { return __uint_as_float(pack_bf16(v, 0.f) << 16); }
__device__ __forceinline__ float bf_lo(uint32_t w) { return __uint_as_float(w << 16); }
__device__ __forceinline__ float bf_hi(uint32_t w) { return __uint_as_float(w & 0xffff0000u); }
__device__ __forceinline__ float ex2(float v) { float d; asm("ex2.approx.ftz.f32 %0, %1;" : "=f"(d) : "f"(v)); return d; }
__device__ __forceinline__ uint4 lds128(uint32_t a) {
    uint4 v; asm volatile("ld.shared.v4.u32 {%0,%1,%2,%3}, [%4];" : "=r"(v.x), "=r"(v.y), "=r"(v.z), "=r"(v.w) : "r"(a) : "memory"); return v;
}
__device__ __forceinline__ uint2 lds64(uint32_t a) {
    uint2 v; asm volatile("ld.shared.v2.u32 {%0,%1}, [%2];" : "=r"(v.x), "=r"(v.y) : "r"(a) : "memory"); return v;
}
__device__ __forceinline__ uint32_t lds32(uint32_t a) {
    uint32_t v; asm volatile("ld.shared.u32 %0, [%1];" : "=r"(v) : "r"(a) : "memory"); return v;
}
__device__ __forceinline__ void sts64(uint32_t a, uint32_t x, uint32_t y) {
    asm volatile("st.shared.v2.u32 [%0], {%1,%2};" ::"r"(a), "r"(x), "r"(y) : "memory");
}
__device__ __forceinline__ void sts32(uint32_t a, uint32_t x) {
    asm volatile("st.shared.u32 [%0], %1;" ::"r"(a), "r"(x) : "memory");
}
__device__ __forceinline__ void sts16(uint32_t a, uint32_t x) {
    asm volatile("st.shared.u16 [%0], %1;" ::"r"(a), "h"((unsigned short)x) : "memory");
}
__device__ __forceinline__ uint32_t lds16(uint32_t a) {
    unsigned short v; asm volatile("ld.shared.u16 %0, [%1];" : "=h"(v) : "r"(a) : "memory"); return v;
}
__device__ __forceinline__ bool wg_bar_or(int id, bool p) {
    uint32_t r;
    asm volatile("{\n.reg .pred a, b;\nsetp.ne.u32 a, %2, 0;\nbar.red.or.pred b, %1, 128, a;\nselp.u32 %0, 1, 0, b;\n}"
                 : "=r"(r) : "r"(id), "r"((uint32_t)p) : "memory");
    return r != 0;
}
__device__ __forceinline__ uint4 ll_ld(const uint4* p) {
    unsigned long long a, b;
    asm volatile("ld.relaxed.gpu.global.v2.b64 {%0,%1}, [%2];" : "=l"(a), "=l"(b) : "l"(p) : "memory");
    return make_uint4((uint32_t)a, (uint32_t)(a >> 32), (uint32_t)b, (uint32_t)(b >> 32));
}
__device__ __forceinline__ void ll_st(uint4* p, uint32_t v0, uint32_t t0, uint32_t v1, uint32_t t1) {
    unsigned long long a = ((unsigned long long)t0 << 32) | v0, b = ((unsigned long long)t1 << 32) | v1;
    asm volatile("st.relaxed.gpu.global.v2.b64 [%0], {%1,%2};" ::"l"(p), "l"(a), "l"(b) : "memory");
}
template <bool EF>
__device__ __forceinline__ uint4 ll_ldh(const uint4* p) {
    if (!EF) return ll_ld(p);
    unsigned long long a, b;
    asm volatile("ld.relaxed.gpu.global.L2::cache_hint.v2.b64 {%0,%1}, [%2], %3;" : "=l"(a), "=l"(b) : "l"(p), "l"(pol_first()) : "memory");
    return make_uint4((uint32_t)a, (uint32_t)(a >> 32), (uint32_t)b, (uint32_t)(b >> 32));
}
template <bool EF>
__device__ __forceinline__ void ll_sth(uint4* p, uint32_t v0, uint32_t t0, uint32_t v1, uint32_t t1) {
    if (!EF) { ll_st(p, v0, t0, v1, t1); return; }
    unsigned long long a = ((unsigned long long)t0 << 32) | v0, b = ((unsigned long long)t1 << 32) | v1;
    asm volatile("st.relaxed.gpu.global.L2::cache_hint.v2.b64 [%0], {%1,%2}, %3;" ::"l"(p), "l"(a), "l"(b), "l"(pol_first()) : "memory");
}
__device__ __forceinline__ void bar_sync(int id, int n) { asm volatile("bar.sync %0, %1;" ::"r"(id), "r"(n) : "memory"); }
__device__ __forceinline__ void bar_arrive(int id, int n) { asm volatile("bar.arrive %0, %1;" ::"r"(id), "r"(n) : "memory"); }
__device__ __forceinline__ void delay_cycles(int n) {
    if (n > 0) {
        uint32_t t0, t1;
        asm volatile("mov.u32 %0, %%clock;" : "=r"(t0));
        do { asm volatile("mov.u32 %0, %%clock;" : "=r"(t1)); } while (t1 - t0 < (uint32_t)n);
    }
}
__device__ __forceinline__ int tid_now() {
    int t; asm volatile("mov.u32 %0, %%tid.x;" : "=r"(t)); return t;
}
__device__ __forceinline__ bool mbar_test(uint32_t bar, uint32_t parity) {
    uint32_t ok;
    asm volatile("{\n.reg .pred p;\nmbarrier.test_wait.parity.shared::cta.b64 p, [%1], %2;\nselp.u32 %0, 1, 0, p;\n}"
                 : "=r"(ok) : "r"(bar), "r"(parity) : "memory");
    return ok != 0;
}

struct Acc {
    float o[2][4];
    float l[4];
    float m0, m1;
};

constexpr float SCALE_LOG2 = 0.08838834764831845f * 1.4426950408889634f;

__device__ __forceinline__ void softmax_step(float* s, Acc& a, uint32_t p_wr, uint32_t mx, int barid, int lane, int wj) {
#pragma unroll
    for (int i = 0; i < 4; i++) s[i] *= SCALE_LOG2;
    bool over = fmaxf(s[0], s[2]) > a.m0 || fmaxf(s[1], s[3]) > a.m1;
    {
        uint32_t b0 = movm(pack_bf16(ex2(s[0] - a.m0), ex2(s[1] - a.m1)));
        uint32_t b1 = movm(pack_bf16(ex2(s[2] - a.m0), ex2(s[3] - a.m1)));
        if (lane < 16) sts64(p_wr, b0, b1);
    }
    if (wg_bar_or(barid, over)) {
        float x0 = fmaxf(s[0], s[2]), x1 = fmaxf(s[1], s[3]);
#pragma unroll
        for (int d = 4; d < 32; d <<= 1) {
            x0 = fmaxf(x0, __shfl_xor_sync(0xffffffffu, x0, d));
            x1 = fmaxf(x1, __shfl_xor_sync(0xffffffffu, x1, d));
        }
        if (lane < 2) sts64(mx + wj * 16 + lane * 8, __float_as_uint(x0), __float_as_uint(x1));
        wg_bar_or(barid, false);
        float n0 = a.m0, n1 = a.m1;
#pragma unroll
        for (int j = 0; j < 4; j++) {
            uint2 v = lds64(mx + j * 16 + (lane & 1) * 8);
            n0 = fmaxf(n0, __uint_as_float(v.x));
            n1 = fmaxf(n1, __uint_as_float(v.y));
        }
        float f0 = ex2(a.m0 - n0), f1 = ex2(a.m1 - n1);
        a.m0 = n0; a.m1 = n1;
        a.o[0][0] *= f0; a.o[0][2] *= f0; a.o[1][0] *= f0; a.o[1][2] *= f0; a.l[0] *= f0; a.l[2] *= f0;
        a.o[0][1] *= f1; a.o[0][3] *= f1; a.o[1][1] *= f1; a.o[1][3] *= f1; a.l[1] *= f1; a.l[3] *= f1;
        uint32_t b0 = movm(pack_bf16(ex2(s[0] - n0), ex2(s[1] - n1)));
        uint32_t b1 = movm(pack_bf16(ex2(s[2] - n0), ex2(s[3] - n1)));
        if (lane < 16) sts64(p_wr, b0, b1);
        wg_bar_or(barid, false);
    }
}

template <int NT>
__device__ __forceinline__ void first_max(float (*s)[4], Acc& a, uint32_t mx, int barid, int lane, int wj) {
    float x0 = __int_as_float(0xff800000), x1 = x0;
#pragma unroll
    for (int j = 0; j < NT; j++) {
#pragma unroll
        for (int i = 0; i < 4; i++) s[j][i] *= SCALE_LOG2;
        x0 = fmaxf(x0, fmaxf(s[j][0], s[j][2]));
        x1 = fmaxf(x1, fmaxf(s[j][1], s[j][3]));
    }
#pragma unroll
    for (int d = 4; d < 32; d <<= 1) {
        x0 = fmaxf(x0, __shfl_xor_sync(0xffffffffu, x0, d));
        x1 = fmaxf(x1, __shfl_xor_sync(0xffffffffu, x1, d));
    }
    if (lane < 2) sts64(mx + wj * 16 + lane * 8, __float_as_uint(x0), __float_as_uint(x1));
    wg_bar_or(barid, false);
#pragma unroll
    for (int j = 0; j < 4; j++) {
        uint2 v = lds64(mx + j * 16 + (lane & 1) * 8);
        x0 = fmaxf(x0, __uint_as_float(v.x));
        x1 = fmaxf(x1, __uint_as_float(v.y));
    }
    a.m0 = x0; a.m1 = x1;
#pragma unroll
    for (int i = 0; i < 4; i++) { a.o[0][i] = 0.f; a.o[1][i] = 0.f; a.l[i] = 0.f; }
}
__device__ __forceinline__ uint2 p_frag(const float* s, const Acc& a) {
    return make_uint2(movm(pack_bf16(ex2(s[0] - a.m0), ex2(s[1] - a.m1))), movm(pack_bf16(ex2(s[2] - a.m0), ex2(s[3] - a.m1))));
}
__device__ __forceinline__ void qk_regs(float* s, const uint32_t* rk, uint32_t q_rd) {
    float s2[4] = {0.f, 0.f, 0.f, 0.f};
    s[0] = s[1] = s[2] = s[3] = 0.f;
#pragma unroll
    for (int x = 0; x < 4; x++) {
        uint4 q = lds128(q_rd + x * 256);
        mma(s, rk + x * 8, q.x, q.y);
        mma(s2, rk + x * 8 + 4, q.z, q.w);
    }
#pragma unroll
    for (int i = 0; i < 4; i++) s[i] += s2[i];
}
__device__ __forceinline__ void qk_smem(float* s, uint32_t kb, uint32_t q_rd) {
    float s2[4] = {0.f, 0.f, 0.f, 0.f};
    s[0] = s[1] = s[2] = s[3] = 0.f;
#pragma unroll
    for (int h = 0; h < 2; h++) {
        uint32_t a[16];
#pragma unroll
        for (int j = 0; j < 4; j++) ldsm4(a + j * 4, (kb ^ (j << 5)) + h * 8192);
        __syncwarp();
        const uint4 q0 = lds128(q_rd + h * 512), q1 = lds128(q_rd + h * 512 + 256);
        mma(s, a, q0.x, q0.y);
        mma(s2, a + 4, q0.z, q0.w);
        mma(s, a + 8, q1.x, q1.y);
        mma(s2, a + 12, q1.z, q1.w);
    }
#pragma unroll
    for (int i = 0; i < 4; i++) s[i] += s2[i];
}
__device__ __forceinline__ void pv_regs(Acc& a, const uint32_t* rv, uint32_t p_rd) {
    const uint32_t ones[4] = {0x3f803f80u, 0x3f803f80u, 0x3f803f80u, 0x3f803f80u};
#pragma unroll
    for (int y = 0; y < 2; y++) {
        uint4 p = lds128(p_rd + y * 256);
        mma(a.o[0], rv + y * 16, p.x, p.y);
        mma(a.o[1], rv + y * 16 + 4, p.x, p.y);
        mma(a.l, ones, p.x, p.y);
        mma(a.o[0], rv + y * 16 + 8, p.z, p.w);
        mma(a.o[1], rv + y * 16 + 12, p.z, p.w);
        mma(a.l, ones, p.z, p.w);
    }
}
__device__ __forceinline__ void load_vpre(uint32_t* f, uint32_t vb) {
#pragma unroll
    for (int kk = 0; kk < VPRE; kk++) {
        ldsm4t(f + kk * 8, vb + kk * 2048);
        ldsm4t(f + kk * 8 + 4, (vb ^ 32) + kk * 2048);
    }
}
__device__ __forceinline__ void pv_smem(Acc& a, uint32_t* f, uint32_t vb, uint32_t p_rd) {
    const uint32_t ones[4] = {0x3f803f80u, 0x3f803f80u, 0x3f803f80u, 0x3f803f80u};
#pragma unroll
    for (int y = 0; y < 2; y++) {
#pragma unroll
        for (int j = 0; j < 2; j++)
            if (2 * y + j >= VPRE) {
                ldsm4t(f + j * 8, vb + (2 * y + j) * 2048);
                ldsm4t(f + j * 8 + 4, (vb ^ 32) + (2 * y + j) * 2048);
            }
        __syncwarp();
        const uint4 pp = lds128(p_rd + y * 256);
        mma(a.o[0], f, pp.x, pp.y);
        mma(a.o[1], f + 4, pp.x, pp.y);
        mma(a.l, ones, pp.x, pp.y);
        mma(a.o[0], f + 8, pp.z, pp.w);
        mma(a.o[1], f + 12, pp.z, pp.w);
        mma(a.l, ones, pp.z, pp.w);
    }
}
__device__ __forceinline__ uint32_t k_offset(uint32_t slots, int wj, int lane) {
    const int row = wj * 16 + (lane & 7) + ((lane >> 3) & 1) * 8;
    return slots + row * 128 + (((lane >> 4) ^ (row & 7)) << 4);
}
__device__ __forceinline__ uint32_t v_offset(uint32_t slots, int wj, int lane) {
    const int key = (lane & 7) + (lane >> 4) * 8, cg = wj * 4 + ((lane >> 3) & 1);
    return slots + (cg >> 3) * 8192 + key * 128 + (((cg & 7) ^ (key & 7)) << 4);
}
__device__ __forceinline__ void load_kfrag(uint32_t* rk, uint32_t kb) {
#pragma unroll
    for (int ks = 0; ks < 8; ks++) ldsm4(rk + ks * 4, (kb ^ ((ks & 3) << 5)) + (ks >> 2) * 8192);
}

template <int NPRE>
__device__ __forceinline__ void ln_gemv_part(uint32_t (*f)[8], uint32_t a0, uint32_t a1, uint32_t kstride, uint32_t x01,
                                             uint32_t x23, int tid) {
    const int lane = tid & 31, wq = tid >> 5, t = lane & 3, g = lane >> 2;
    float c0[4] = {0.f, 0.f, 0.f, 0.f}, c1[4] = {0.f, 0.f, 0.f, 0.f};
#pragma unroll
    for (int ks = 0; ks < 4; ks++) {
        uint32_t* ff = f[ks % NPRE];
        if (ks >= NPRE) {
            ldsm4t(ff, a0 + ks * kstride);
            ldsm4t(ff + 4, a1 + ks * kstride);
        }
        uint32_t xa = __shfl_sync(0xffffffffu, x01, ks * 4 + t), xb = __shfl_sync(0xffffffffu, x23, ks * 4 + t);
        if (g & 1) xa = xb = 0x3f803f80u;
        mma(c0, ff, xa, xb);
        mma(c1, ff + 4, xa, xb);
    }
    float a = bf_lo(x01), b = bf_hi(x01), c = bf_lo(x23), d = bf_hi(x23);
    float su = (a + b) + (c + d), sq = fmaf(a, a, b * b) + fmaf(c, c, d * d);
    {
        float keep = (lane & 8) ? sq : su, send = (lane & 8) ? su : sq;
        keep += __shfl_xor_sync(0xffffffffu, send, 8);
#pragma unroll
        for (int k = 4; k > 0; k >>= 1) keep += __shfl_xor_sync(0xffffffffu, keep, k);
        if ((lane & 23) == 0) sts32(SM_RED + (lane >> 3) * 32 + wq * 4, __float_as_uint(keep));
    }
    float y = (t & 2) ? ((t & 1) ? c1[2] : c1[0]) : ((t & 1) ? c0[2] : c0[0]);
    float z = (t & 2) ? ((t & 1) ? c1[3] : c1[1]) : ((t & 1) ? c0[3] : c0[1]);
    sts64(SM_Q + wq * 256 + (t * 8 + g) * 8, __float_as_uint(y), __float_as_uint(z));
}
__device__ __forceinline__ float sum4(uint4 u) {
    return (__uint_as_float(u.x) + __uint_as_float(u.y)) + (__uint_as_float(u.z) + __uint_as_float(u.w));
}
__device__ __forceinline__ float ln_gemv_fin(int lane) {
    float mean = (sum4(lds128(SM_RED)) + sum4(lds128(SM_RED + 16))) * (1.f / 512.f);
    float sq = (sum4(lds128(SM_RED + 32)) + sum4(lds128(SM_RED + 48))) * (1.f / 512.f);
    float rstd = rsqrtf(fmaxf(sq - mean * mean, 0.f) + 1e-5f);
    float y = 0.f, cs = 0.f;
#pragma unroll
    for (int j = 0; j < 8; j += 2) {
        uint2 u = lds64(SM_Q + j * 256 + lane * 8), v = lds64(SM_Q + j * 256 + 256 + lane * 8);
        y += __uint_as_float(u.x) + __uint_as_float(v.x);
        cs += __uint_as_float(u.y) + __uint_as_float(v.y);
    }
    return (y - mean * cs) * rstd;
}
template <int NPROD, bool SIGNAL, int TSI>
__device__ __forceinline__ void finish_cols(const uint4* src, uint32_t tag, int tid, int delay, uint32_t& w01, uint32_t& w23) {
    const int lane = tid & 31, wq = tid >> 5;
    const uint32_t dst = SM_RED + 64 + wq * 16 + lane * 4;
    const bool two = tid + 128 < 2 * NPROD;
    src += tid;
    delay_cycles(delay);
    uint4 u = ll_ld(src), v = make_uint4(0, tag, 0, tag);
    if (two) v = ll_ld(src + 128);
    uint32_t it = 0;
    while (true) {
        const bool oku = u.y == tag && u.w == tag, okv = v.y == tag && v.w == tag;
        if (oku && okv) break;
        if (++it > SPIN_LIMIT) __trap();
        if (!oku) u = ll_ld(src);
        if (!okv) v = ll_ld(src + 128);
    }
    __syncwarp();
    TS(TSI);
    if (SIGNAL && wq == 0) bar_arrive(7, 160);
    const float v0 = __uint_as_float(u.x) + __uint_as_float(v.x), v1 = __uint_as_float(u.z) + __uint_as_float(v.z);
    float keep = (lane & 2) ? v1 : v0, send = (lane & 2) ? v0 : v1;
    keep += __shfl_xor_sync(0xffffffffu, send, 2);
#pragma unroll
    for (int k = 4; k < 32; k <<= 1) keep += __shfl_xor_sync(0xffffffffu, keep, k);
    if (lane < 4) sts32(dst, __float_as_uint(keep));
    if (wq != 0) {
        bar_arrive(3, 128);
    } else {
        const uint2 xr = lds64(SM_XR);
        bar_sync(3, 128);
        const uint4 a = lds128(SM_RED + 64), b = lds128(SM_RED + 80), c = lds128(SM_RED + 96), d = lds128(SM_RED + 112);
#define COL(f) ((__uint_as_float(a.f) + __uint_as_float(b.f)) + (__uint_as_float(c.f) + __uint_as_float(d.f)))
        const uint32_t y01 = pack_bf16(COL(x), COL(y)), y23 = pack_bf16(COL(z), COL(w));
#undef COL
        w01 = pack_bf16(bf_lo(xr.x) + bf_lo(y01), bf_hi(xr.x) + bf_hi(y01));
        w23 = pack_bf16(bf_lo(xr.y) + bf_lo(y23), bf_hi(xr.y) + bf_hi(y23));
    }
}

__device__ __forceinline__ int unit_head(int cta, int wg) { return cta < 128 ? ((cta + (cta >> 3)) & 7) : (cta - 128) * 2 + wg; }
__device__ __forceinline__ int unit_index(int cta, int wg) { return cta < 128 ? (cta >> 3) * 2 + wg : 32; }
__device__ __forceinline__ void issue_item(int j, const Maps& tm, int tb, int ui, bool hasX, uint32_t slots, uint32_t bars) {
    int slot = (int)((0x0165432165432ull >> (4 * j)) & 15);
    int tile = j < 10 ? (j >> 1) * NUNIT + ui : T_X + (ui >> 1);
    if (j == 12 || (j >= 10 && !hasX)) { tile = T_DYN0 + ui; slot = j & 1; }
    if (j == 12 && !hasX) return;
    tma_tile((j & 1) ? &tm.v : &tm.k, tb + tile, slots + slot * SLOT, bars + slot * 8);
}
__device__ __forceinline__ void gu_box(const Maps& tm, int cta, int j) {
    tma_2d(j < 2 ? &tm.wg : &tm.wu, cta * 16, (j & 1) * 256, SM_SLOTS + (j & 1) * 7 * SLOT + (j >> 1) * 8192, SM_WBAR);
}
__device__ __forceinline__ void wq_box(const Maps& tm, int cta, int j) {
    tma_2d(&tm.wq, cta * 32, j * 256, SM_SLOTS + j * 7 * SLOT, SM_WBAR);
}
__device__ __forceinline__ void issue_tail_weights(const Maps& tm, int cta, int wg) {
    const uint32_t slots = SM_SLOTS + wg * 7 * SLOT;
    expect_tx(SM_TBAR, cta < 112 ? 2 * SLOT : SLOT);
    asm volatile("cp.async.bulk.tensor.3d.shared::cluster.global.mbarrier::complete_tx::bytes.L2::cache_hint "
                 "[%0], [%1, {%2, %3, %4}], [%5], %6;"
                 ::"r"(slots + 3 * SLOT), "l"(&tm.wo), "r"(0), "r"(cta * 32 + wg * 16), "r"(0), "r"(SM_TBAR), "l"(pol_first()) : "memory");
    if (cta < 112) {
        tma_2d(&tm.wg, cta * 16, wg * 256, slots + 5 * SLOT, SM_TBAR);
        tma_2d(&tm.wu, cta * 16, wg * 256, slots + 5 * SLOT + 8192, SM_TBAR);
    }
}
__device__ __forceinline__ uint32_t draw_ticket(const Params& p, int cta, int ph) {
    const int wg = tid_now() >> 7;
    return atomicAdd(&g_s.ticket[ph][unit_head(cta, wg)][0], 1);
}
#define DESC(sk, sv, wk, wv) ((uint32_t)((sk) | ((sv) << 3) | ((wk) << 6) | ((wv) << 7)))
constexpr uint32_t A_LDK = 1u << 20, A_LDV = 1u << 21, A_KEEP = 1u << 22, A_WGT = 1u << 24, A_DRAW = 1u << 26;
constexpr uint32_t S_STREAM = 1u << 24, S_SINCE = 1u << 26, S_XISS = 1u << 19, S_FREE = 1u << 20, S_WGT = 1u << 21, S_END = 1u << 23;

template <int NPRE, bool WAITW>
__device__ __forceinline__ uint4 gather_x(const uint4* src, uint32_t tag, uint32_t (*f)[8], uint32_t a0, uint32_t a1,
                                          uint32_t kstride, uint32_t wpar, int wq) {
    if (wq) bar_sync(6, 256); else bar_arrive(6, 256);
    delay_cycles(D_AG);
    uint4 v = ll_ld(src);
    if (WAITW) mbar_wait(SM_WBAR, wpar);
    __syncwarp();
#pragma unroll
    for (int ks = 0; ks < NPRE; ks++) {
        ldsm4t(f[ks], a0 + ks * kstride);
        ldsm4t(f[ks] + 4, a1 + ks * kstride);
    }
    uint32_t it = 0;
    while (v.y != tag || v.w != tag) {
        if (++it > SPIN_LIMIT) __trap();
        v = ll_ld(src);
    }
    __syncwarp();
    return v;
}

__device__ __forceinline__ uint4* part_dst(const Params& p, int head, int ui, int tid) {
    const int lane = tid & 31, g = lane >> 2, t = lane & 3;
    return &g_s.part[(head * 4 + 2 * (t & 1) + (t >> 1)) * 4 + ((tid >> 5) & 3)][g >> 1][ui][g & 1];
}
__device__ __forceinline__ void prewrite(const Params& p, int cta, uint32_t z) {
    const int tid = tid_now(), lane = tid & 31, wq = tid >> 5, g = lane >> 2, t = lane & 3;
    ll_st(&g_s.r[wq * 16 + t * 4 + (g >> 1)][cta][g & 1], 0, z, 0, z);
    if (tid < 2 * XREP) {
        ll_st(&g_s.x1[tid >> 1][cta][tid & 1], 0, z, 0, z);
        ll_st(&g_s.x2[tid >> 1][cta][tid & 1], 0, z, 0, z);
    }
    if (tid < 8) ll_st(&g_s.q[1][0][cta >> 4][((cta & 3) * 16 + ((cta >> 2) & 3) * 4) * 2 + tid], 0, z, 0, z);
}
template <bool PF>
__device__ __forceinline__ void wait_all_done(const Params& p, int cta, uint32_t target) {
    if (tid_now() == 0) {
        uint32_t it = 0;
        bool pf = PF;
        while (true) {
            uint32_t v;
            asm volatile("ld.relaxed.gpu.global.u32 %0, [%1];" : "=r"(v) : "l"(&g_s.done[0]) : "memory");
            const int rem = (int)(target - v);
            if (pf && rem <= PF_REM) {
                pf = false;
                l2_prefetch(p.wg + (size_t)cta * 14336, 14336, pol_first());
                l2_prefetch(p.wu + (size_t)cta * 14336, 14336, pol_first());
                if (WPF & 64) l2_prefetch(p.wq + (size_t)cta * 32768, 32768, pol_first());
            }
            if (rem <= 0) break;
            if (++it > SPIN_LIMIT) __trap();
            if (rem > 16) delay_cycles(400);
        }
        delay_cycles(D_H1);
    }
    __syncthreads();
}

template <bool TAIL>
__device__ __forceinline__ void gemv_chain(const Maps& tm, const Params& p, const int cta, const uint32_t tag) {
    constexpr uint32_t Z_WO = SM_SLOTS + (TAIL ? 3 : 0) * SLOT, Z_GU = SM_SLOTS + (TAIL ? 5 : 0) * SLOT;
    constexpr uint32_t Z_WD = SM_SLOTS + 13 * SLOT;
    [[maybe_unused]] constexpr int TB = TAIL ? 16 : 0;
    {
        const int tid = tid_now(), lane = tid & 31, wq = tid >> 5, g = lane >> 2, t = lane & 3;
        const uint32_t t16 = tag & 0xffffu;
        const uint4* src = &g_s.part[cta][wq][lane & 15][lane >> 4];
        const bool three = (lane & 15) == 0;
        wait_all_done<!TAIL && (WPF & 32)>(p, cta, ((tag >> 2) * 2 + (TAIL ? 2 : 1)) * (2 * NCTA));
        TS(TB + 14);
        uint4 a = ll_ldh<(PART_EF & 2) != 0>(src), b = ll_ldh<(PART_EF & 2) != 0>(src + 32), e = make_uint4(0, 0xff800000u | t16, 0, t16);
        if (three) e = ll_ldh<(PART_EF & 2) != 0>(src + 64);
        const uint32_t wa0 = Z_WO + wq * 2048 + ((lane & 7) + (lane >> 4) * 8) * 128 + ((((lane >> 3) & 1) ^ (lane & 7)) << 4);
        uint32_t f0[4][4], f1[4][4];
        if (TAIL) {
            mbar_wait(SM_TBAR, 0);
            __syncwarp();
#pragma unroll
            for (int mt = 0; mt < 4; mt++) {
                ldsm4t(f0[mt], wa0 ^ (mt << 5));
                ldsm4t(f1[mt], (wa0 ^ (mt << 5)) + 7 * SLOT);
            }
        }
        {
            uint32_t it = 0;
            while (true) {
                const bool oka = ((a.y ^ t16) | (a.w ^ t16)) << 16 == 0, okb = ((b.y ^ t16) | (b.w ^ t16)) << 16 == 0;
                const bool oke = ((e.y ^ t16) | (e.w ^ t16)) << 16 == 0;
                if (oka && okb && oke) break;
                if (++it > SPIN_LIMIT) __trap();
                if (!oka) a = ll_ldh<(PART_EF & 2) != 0>(src);
                if (!okb) b = ll_ldh<(PART_EF & 2) != 0>(src + 32);
                if (!oke) e = ll_ldh<(PART_EF & 2) != 0>(src + 64);
            }
        }
        __syncwarp();
        TS(TB + 0);
        const float la = __uint_as_float(__byte_perm(a.w, a.y, 0x7632)), lb = __uint_as_float(__byte_perm(b.w, b.y, 0x7632));
        const float le = __uint_as_float(__byte_perm(e.w, e.y, 0x7632));
        float mm;
        {
            int k = __float_as_int(fmaxf(fmaxf(la, lb), le));
            k ^= (k >> 31) & 0x7fffffff;
            k = __reduce_max_sync(0xffffffffu, k);
            k ^= (k >> 31) & 0x7fffffff;
            mm = __int_as_float(k);
        }
        const float wa = ex2(la - mm), wb = ex2(lb - mm), we = ex2(le - mm);
        const float v0 = fmaf(we, __uint_as_float(e.x), fmaf(wb, __uint_as_float(b.x), wa * __uint_as_float(a.x)));
        const float v1 = fmaf(we, __uint_as_float(e.z), fmaf(wb, __uint_as_float(b.z), wa * __uint_as_float(a.z)));
        float ws = wa + wb + we;
        float kk = (lane & 8) ? v1 : v0;
        kk += __shfl_xor_sync(0xffffffffu, (lane & 8) ? v0 : v1, 8);
        ws += __shfl_xor_sync(0xffffffffu, ws, 8);
        if (!TAIL) {
            mbar_wait(SM_WBAR, 1);
            __syncwarp();
#pragma unroll
            for (int mt = 0; mt < S1_NPRE; mt++) {
                ldsm4t(f0[mt], wa0 ^ (mt << 5));
                ldsm4t(f1[mt], (wa0 ^ (mt << 5)) + 7 * SLOT);
            }
        }
#pragma unroll
        for (int k = 4; k > 0; k >>= 1) {
            kk += __shfl_xor_sync(0xffffffffu, kk, k);
            ws += __shfl_xor_sync(0xffffffffu, ws, k);
        }
        {
            float r; asm("rcp.approx.ftz.f32 %0, %1;" : "=f"(r) : "f"(ws));
            const uint32_t o = pack_bf16(kk * r, 0.f);
            if ((lane & 7) == 0) sts16(SM_RED + 256 + (wq & 3) * 16 + (wq >> 2) * 8 + ((lane >> 3) & 1) * 4 + (lane >> 4) * 2, o);
        }
        uint4* out = &g_s.r[wq * 16 + t * 4 + (g >> 1)][cta][g & 1];
        __syncthreads();
        TS(TB + 1);
        const uint4 ob = lds128(SM_RED + 256 + t * 16);
        float c0[4] = {0.f, 0.f, 0.f, 0.f}, c1[4] = {0.f, 0.f, 0.f, 0.f};
#pragma unroll
        for (int mt = 0; mt < 4; mt++) {
            constexpr int NP = TAIL ? 4 : S1_NPRE;
            uint32_t* g0 = f0[mt % NP];
            uint32_t* g1 = f1[mt % NP];
            if (mt >= NP) {
                ldsm4t(g0, wa0 ^ (mt << 5));
                ldsm4t(g1, (wa0 ^ (mt << 5)) + 7 * SLOT);
            }
            const bool mine = (g >> 1) == mt;
            mma(c0, g0, mine ? ob.x : 0u, mine ? ob.y : 0u);
            mma(c1, g1, mine ? ob.z : 0u, mine ? ob.w : 0u);
        }
        ll_st(out, __float_as_uint(c0[0] + c1[0]), tag, __float_as_uint(c0[2] + c1[2]), tag);
        TS(TB + 2);
        if (!TAIL) {
            if (tid < 128) {
                bar_arrive(4, 256);
            } else {
                bar_sync(4, 256);
                if (lane == 0) {
                    if (wq < 6) expect_tx(SM_WBAR, SLOT);
                    if (cta < 112 && wq - 4 < GU_FIRST) gu_box(tm, cta, wq - 4);
                    if (WPF & 8) l2_prefetch(p.wq + (size_t)(cta * 4 + wq - 4) * 8192, 8192, pol_first());
                }
                __syncwarp();
                bar_sync(7, 160);
                if (lane == 0) {
                    if (cta < 112) { if (wq - 4 >= GU_FIRST) gu_box(tm, cta, wq - 4); }
                    else if (wq < 6) wq_box(tm, cta, wq - 4);
                }
                __syncwarp();
            }
        }
    }
    {
        const int tid = tid_now();
        if (tid < 128) {
            uint32_t w01 = 0, w23 = 0;
            uint4* out = &g_s.x1[(tid >> 1) & (XREP - 1)][cta][tid & 1];
            finish_cols<128, !TAIL, TB + 15>(&g_s.r[cta][0][0], tag, tid, D_RS, w01, w23);
            if (tid < 2 * XREP) ll_st(out, w01, tag, w23, tag);
            if (tid == 0) sts64(SM_XR, w01, w23);
            __syncwarp();
        }
        TS(TB + 3);
    }
    if (cta < 112) {
        const int tid = tid_now(), lane = tid & 31, wq = tid >> 5, g = lane >> 2, t = lane & 3;
        constexpr int NPRE = TAIL ? 4 : MID_NPRE;
        uint32_t f[NPRE][8];
        const int row = (wq & 3) * 64 + (lane & 7) + (lane >> 4) * 8;
        const uint32_t a0 = Z_GU + (wq >> 2) * 7 * SLOT + row * 32 + ((((lane >> 3) ^ (lane >> 2)) & 1) << 4);
        if (!TAIL) mbar_wait(SM_BAR + 13 * 8, 1);
        const uint4 xv = gather_x<NPRE, !TAIL>(&g_s.x1[cta & (XREP - 1)][wq * 16 + (lane & 15)][0], tag, f, a0, a0 + 8192, 512, 0, wq);
        TS(TB + 4);
        ln_gemv_part<NPRE>(f, a0, a0 + 8192, 512, xv.x, xv.z, tid);
        const uint32_t wd0 = Z_WD + wq * 2048 + ((lane & 7) + (lane >> 4) * 8) * 128 + ((((lane >> 3) & 1) ^ (lane & 7)) << 4);
        uint32_t d[4][4];
        constexpr int DPRE = TAIL ? 4 : 2;
#pragma unroll
        for (int mt = 0; mt < DPRE; mt++) ldsm4t(d[mt], wd0 ^ (mt << 5));
        uint4* out = &g_s.r[wq * 16 + t * 4 + (g >> 1)][cta][g & 1];
        __syncthreads();
        TS(TB + 5);
        const float r = bf16r(ln_gemv_fin(lane));
        const float up = __shfl_down_sync(0xffffffffu, r, 16);
#pragma unroll
        for (int mt = DPRE; mt < 4; mt++) ldsm4t(d[mt], wd0 ^ (mt << 5));
        const float h = (r > 0.f ? r : 0.f * r) * up;
        const float h0 = __shfl_sync(0xffffffffu, h, 2 * t), h1 = __shfl_sync(0xffffffffu, h, 2 * t + 1);
        const float h2 = __shfl_sync(0xffffffffu, h, 2 * t + 8), h3 = __shfl_sync(0xffffffffu, h, 2 * t + 9);
        const uint32_t b0 = pack_bf16(h0, h1), b1 = pack_bf16(h2, h3);
        float c0[4] = {0.f, 0.f, 0.f, 0.f}, c1[4] = {0.f, 0.f, 0.f, 0.f};
#pragma unroll
        for (int mt = 0; mt < 4; mt++) {
            const bool mine = (g >> 1) == mt;
            mma((mt & 1) ? c1 : c0, d[mt], mine ? b0 : 0u, mine ? b1 : 0u);
        }
        ll_st(out, __float_as_uint(c0[0] + c1[0]), ~tag, __float_as_uint(c0[2] + c1[2]), ~tag);
        TS(TB + 6);
    }
    {
        const int tid = tid_now();
        if (tid < 128) {
            uint32_t w01 = 0, w23 = 0;
            uint4* out = &g_s.x2[(tid >> 1) & (XREP - 1)][cta][tid & 1];
            finish_cols<112, !TAIL, TAIL ? 43 : 42>(&g_s.r[cta][0][0], ~tag, tid, cta < 112 ? D_RS : D_RS + D_SKIP, w01, w23);
            if (!TAIL) {
                if (tid < 2 * XREP) ll_st(out, w01, tag, w23, tag);
                if (tid == 0) sts64(SM_XR, w01, w23);
            } else if (tid < 32) {
                if (tid < 2) *reinterpret_cast<uint32_t*>(p.out + (cta >> 2) * 16 + (cta & 3) * 2 + tid * 8) = tid ? w23 : w01;
                if (cta == 0) {
                    if (tid < 16) g_s.ticket[tid >> 3][tid & 7][0] = 0;
                    if (tid == 16) g_s.epoch = (tag >> 2) + 1;
                }
            }
            __syncwarp();
        } else if (!TAIL) {
            const int j = (tid >> 5) - 4;
            const bool mine = cta < 112 && j < 2 && (tid & 31) == 0;
            if (mine) {
                expect_tx(SM_WBAR, SLOT);
                if (j < WQ_FIRST) wq_box(tm, cta, j);
            }
            __syncwarp();
            bar_sync(7, 160);
            if (mine && j >= WQ_FIRST) wq_box(tm, cta, j);
            if (PF_T0 && j >= 2 && (tid & 31) == 0) {
                const size_t o = (size_t)(unit_head(cta, j - 2) * NTILE + T_DYN0 + unit_index(cta, j - 2)) * SLOT;
                l2_prefetch(p.k + o, SLOT, pol_first());
                if (PF_T0 > 1) l2_prefetch(p.v + o, SLOT, pol_first());
            }
            __syncwarp();
        }
        TS(TB + 7);
    }
}

template <int PH>
__device__ __forceinline__ void q_stage(const Params& p, const int cta, const uint32_t tag, uint32_t x01 = 0, uint32_t x23 = 0) {
    const int tid = tid_now(), lane = tid & 31, wq = tid >> 5;
    constexpr int NPRE = PH ? MID_NPRE : 4;
    uint32_t f[NPRE][8];
    const int row = (wq & 3) * 64 + (lane & 7) + (lane >> 4) * 8;
    const uint32_t a0 = SM_SLOTS + (wq >> 2) * 7 * SLOT + row * 64 + ((((lane >> 3) & 1) ^ ((lane >> 1) & 3)) << 4);
    uint4 xv;
    if (PH) {
        xv = gather_x<NPRE, true>(&g_s.x2[cta & (XREP - 1)][wq * 16 + (lane & 15)][0], tag, f, a0, a0 ^ 32, 1024, cta < 112 ? 1 : 0, wq);
    } else {
        xv.x = x01; xv.z = x23;
        mbar_wait(SM_WBAR, 0);
        __syncwarp();
#pragma unroll
        for (int ks = 0; ks < NPRE; ks++) {
            ldsm4t(f[ks], a0 + ks * 1024);
            ldsm4t(f[ks] + 4, (a0 ^ 32) + ks * 1024);
        }
    }
    TS(8 + (PH ? 0 : 24));
    ln_gemv_part<NPRE>(f, a0, a0 ^ 32, 1024, xv.x, xv.z, tid);
    uint4* out = &g_s.q[PH][(lane >> 3) & 1][cta >> 4][((cta & 3) * 16 + ((cta >> 2) & 3) * 4) * 2 + (lane & 7)];
    __syncthreads();
    if (wq == 0) {
        const float r = ln_gemv_fin(lane);
        const int src = (lane & 1) * 16 + ((lane >> 1) & 3) * 2;
        const float q0 = __shfl_sync(0xffffffffu, r, src), q1 = __shfl_sync(0xffffffffu, r, src + 1);
        const float q2 = __shfl_sync(0xffffffffu, r, src + 8), q3 = __shfl_sync(0xffffffffu, r, src + 9);
        if (lane < 16) ll_st(out, pack_bf16(q0, q1), tag, pack_bf16(q2, q3), tag);
        __syncwarp();
        bar_arrive(5, 256);
    } else {
        bar_sync(5, 256);
    }
    TS(9 + (PH ? 0 : 24));
}
template <int PH>
__device__ __forceinline__ void gather_q(const Params& p, int cta, int head, uint32_t qbase, uint32_t tag, int barid) {
    const int t7 = tid_now() & 127;
    const uint4* src = &g_s.q[PH][cta >> 7][head][t7];
    if (PH) delay_cycles(D_AG);
    uint4 v = ll_ld(src);
    uint32_t it = 0;
    while (v.y != tag || v.w != tag) {
        if (++it > SPIN_LIMIT) __trap();
        if (PH == 0 || cta >= 128) delay_cycles(200);
        v = ll_ld(src);
    }
    sts64(qbase + t7 * 8, v.x, v.z);
    __syncwarp();
    wg_bar_or(barid, false);
    TS(10 + (PH ? 0 : 24));
}

#define UVARS                                                                              \
    const int wqu = __shfl_sync(0xffffffffu, tid_now() >> 5, 0);                           \
    const int wg = wqu >> 2, wj = wqu & 3;                                                 \
    const int head = unit_head(cta, wg), ui = unit_index(cta, wg), tb = head * NTILE;      \
    [[maybe_unused]] const bool hasX = worker && wg == 0;                                                   \
    const uint32_t slots = SM_SLOTS + wg * 7 * SLOT, bars = SM_BAR + wg * 56;              \
    const int barid = 1 + wg;                                                              \
    const uint32_t qbase = worker ? SM_Q : slots + 6 * SLOT;                               \
    const uint32_t rec = SM_ST + wg * 16;   \
    const uint32_t mx = SM_MX + wg * 64;
#define Q_RD (qbase + (lane & 15) * 16)
#define P_RD (SM_P + wg * 512 + (lane & 15) * 16)
#define P_WR (SM_P + wg * 512 + (wj >> 1) * 256 + (wj & 1) * 8 + (lane & 15) * 16)
#define PACE()                                                                                    \
        if (wj == 0 && lane == 0) {                                                               \
            uint32_t st = lds32(rec + 8);                                                         \
            int ki = (st >> 8) & 255;                                                             \
            while (ki < 13 && mbar_test(bars + (ki - PD - 4) * 8, 1)) {                                \
                issue_item(ki, tm, tb, ui, hasX, slots, bars);                                    \
                ki++; if (!hasX && ki == 12) ki = 13;                                             \
            }                                                                                     \
            sts32(rec + 8, (st & ~0xff00u) | ki << 8);                                            \
        }                                                                                         \
        __syncwarp();

template <int ph>
__device__ __forceinline__ void attention_pass(const Maps& tm, const Params& p, const int cta, const uint32_t tag0, Acc& acc,
                                               uint32_t nx, uint32_t ticket) {
        const bool worker = cta < 128;
        UVARS
        uint32_t phbits = __shfl_sync(0xffffffffu, lds32(rec + 12), 0);
#pragma unroll 1
        while (true) {
            const int lane = tid_now() & 31;
            const uint32_t desc = nx & 1023;
            const int sk = desc & 7, sv = (desc >> 3) & 7;
            const uint32_t kb = k_offset(slots, wj, lane) + sk * SLOT;
            float s[4];
            if (desc & 64) {
                mbar_wait(bars + sk * 8, (phbits >> sk) & 1);
                phbits ^= 1u << sk;
                if (DBG_U && ph == DBG_PH) TSW(26);
                if ((desc & 512) && wj == 0 && lane == 0) ticket = draw_ticket(p, cta, ph);
                if (ph == 0 && sk) { PACE(); }
                __syncwarp();
            }
            qk_smem(s, kb, Q_RD);
            mbar_wait(bars + sv * 8, (phbits >> sv) & 1);
            phbits ^= 1u << sv;
            if (DBG_U && ph == DBG_PH) TSW(30);
            if (ph == 0 && sk) { PACE(); }
            __syncwarp();
            {
                const uint32_t vb = v_offset(slots, wj, lane) + sv * SLOT;
                uint32_t f[16];
                load_vpre(f, vb);
                softmax_step(s, acc, P_WR, mx, barid, lane, wj);
                pv_smem(acc, f, vb, P_RD);
            }
            if (wj == 0 && lane == 0) {
                uint32_t fifo = lds32(rec + 4), st = lds32(rec + 8);
                uint32_t push = 0, act = 0;
                const int lim = ph ? T_KEEP0 : NTILE;
                if (desc & 256) st -= S_STREAM;
                if (sk == 6) {
                    if (ph == 0) act = (T_DYN0 + ui) << 10 | A_LDV;
                } else if (sk == 3) {
                    st |= S_FREE;
                } else if (sk == 0 || ph != 0) {
                    const int n = st & 255, ki = (st >> 8) & 255;
                    const bool keeps = ph != 0 && ki < n;
                    int tv = NTILE;
                    if (!(st & S_END) && ((st & (3u << 24)) == 0 || (keeps && (st >> 26) < KRATIO && !(fifo & 0x20080200u))))
                        tv = (int)ticket + T_DYN0 + NUNIT;
                    if (tv < lim) {
                        st += S_STREAM;
                        if ((st >> 26) < 7) st += S_SINCE;
                        push = (desc & 63) | 192 | 256;
                        if (ph == 0 && tv >= T_KEEP0) {
                            sts16(SM_KEEP + wg * 64 + n * 2, tv);
                            st++;
                            if (tv < T_KEEPEND) act |= A_KEEP;
                            if (n + 1 >= KEEPCAP) st |= S_END;
                        }
                        if (!(st & S_END)) { if (tv < lim - JIT_WIN) act |= A_DRAW; else push |= 512; }
                        if (worker && (st & (S_FREE | S_WGT)) == S_FREE && tv >= lim - (ph ? TAIL_EARLY : WO_EARLY)) { st |= S_WGT; act |= A_WGT; }
                        act |= tv << 10 | A_LDK | A_LDV;
                    } else if (keeps) {
                        tv = lds16(SM_KEEP + wg * 64 + ki * 2);
                        st = (st + 256) & ~(7u << 26);
                        push = (desc & 63) | 192;
                        act |= tv << 10 | A_LDK | A_LDV;
                    } else if (ph != 0 && hasX && !(st & S_XISS)) {
                        st |= S_XISS;
                        act |= (T_X + (ui >> 1)) << 10 | A_LDV;
                        push = DESC(6, sv, 0, 1);
                    }
                }
                fifo |= push << (fifo == 0 ? 0 : fifo < 1024 ? 10 : 20);
                if (fifo == 0) asm volatile("red.relaxed.gpu.global.add.u32 [%0], 1;" ::"l"(&g_s.done[0]) : "memory");
                sts64(rec, (fifo & 1023) | act, fifo >> 10);
                sts32(rec + 8, st);
            }
            __syncwarp();
            wg_bar_or(barid, false);
            nx = __shfl_sync(0xffffffffu, lds32(rec), 0);
            if ((nx & 1023) == 0) break;
            if (lane == 0) {
                const int gt = tb + ((nx >> 10) & 1023);
                if (wj == 0 && (nx & A_DRAW)) ticket = draw_ticket(p, cta, ph);
                if (wj == 1 && (nx & A_LDK)) {
                    tma_tile(&tm.k, gt, slots + sk * SLOT, bars + sk * 8);
                    if (nx & A_KEEP) l2_prefetch(p.k + (size_t)gt * SLOT, SLOT, pol_normal());
                    TT(ph, head, gt - tb);
                }
                if (wj == 2 && (nx & A_LDV)) {
                    tma_tile(&tm.v, gt, slots + sv * SLOT, bars + sv * 8);
                    if (nx & A_KEEP) l2_prefetch(p.v + (size_t)gt * SLOT, SLOT, pol_normal());
                }
                if (wj == 3 && (nx & A_WGT)) {
                    if (ph != 0) issue_tail_weights(tm, cta, wg);
                    else if (WPF & 1) l2_prefetch(p.wo + (size_t)(cta * 2 + wg) * 16384, 16384, pol_first());
                }
            }
            if (DBG_U && ph == DBG_PH && (nx & A_LDK)) TSW(24);
            __syncwarp();
        }
        const int lane = tid_now() & 31;
        {
            const int e = (lane >> 1) & 1;
            float l = e ? acc.l[1] : acc.l[0], m = e ? acc.m1 : acc.m0;
            float inv; asm("rcp.approx.ftz.f32 %0, %1;" : "=f"(inv) : "f"(l));
            float lg; asm("lg2.approx.ftz.f32 %0, %1;" : "=f"(lg) : "f"(l));
            uint32_t lam = __float_as_uint(m + lg);
            const uint32_t t16 = (tag0 + ph + 1) & 0xffffu;
            uint32_t ta = (lam & 0xffff0000u) | t16, tc = (lam << 16) | t16;
            uint4* dst = part_dst(p, head, ui, wqu * 32 + lane);
            ll_sth<(PART_EF & 1) != 0>(dst, __float_as_uint((e ? acc.o[0][1] : acc.o[0][0]) * inv), ta,
                       __float_as_uint((e ? acc.o[0][3] : acc.o[0][2]) * inv), tc);
            ll_sth<(PART_EF & 1) != 0>(dst + 4 * NUNIT * 2, __float_as_uint((e ? acc.o[1][1] : acc.o[1][0]) * inv), ta,
                                       __float_as_uint((e ? acc.o[1][3] : acc.o[1][2]) * inv), tc);
        }
        if (ph) TSW(38); else TSW(36);
        if (ph != 0) {
            if (wj == 3 && lane == 0 && worker && !(lds32(rec + 8) & S_WGT)) issue_tail_weights(tm, cta, wg);
        } else if (wj == 0 && lane == 0) {
            sts32(rec + 12, phbits);
        }
        __syncwarp();
}

__global__ void __launch_bounds__(256, 1)
fused_kernel(const __grid_constant__ Maps tm, const Params p) {
    extern __shared__ __align__(1024) unsigned char smem_raw[];
    const int cta = blockIdx.x;
    const bool worker = cta < 128;
    uint32_t tag0;
    if ((uint32_t)__cvta_generic_to_shared(smem_raw) != SM_BASE) __trap();
    TS(40);

    uint32_t rk[3][32], rv[3][32];
    Acc acc;
    uint32_t nx, ticket = 0;
    {
        UVARS
        const int lane = tid_now() & 31;
        if (wj == 0 && lane == 0) {
#pragma unroll
            for (int s = 0; s < 7; s++) mbar_init(bars + s * 8, 1);
            mbar_init(SM_WBAR + wg * 8, 2);
            asm volatile("fence.proxy.async.shared::cta;" ::: "memory");
            issue_item(0, tm, tb, ui, hasX, slots, bars);
            issue_item(1, tm, tb, ui, hasX, slots, bars);
            if (hasX) {
                expect_tx(SM_WBAR, SLOT);
                wq_box(tm, cta, 0);
                expect_tx(SM_WBAR, SLOT);
                wq_box(tm, cta, 1);
            }
#pragma unroll
            for (int j = 2; j < PD; j++) issue_item(j, tm, tb, ui, hasX, slots, bars);
            sts64(rec, 0, hasX ? (DESC(4, 5, 1, 1) | DESC(6, 1, 1, 1) << 10 | DESC(0, 1, 1, 1) << 20)
                               : (DESC(4, 5, 1, 1) | DESC(0, 1, 1, 1) << 10));
            sts64(rec + 8, (6 + PD) << 8 | S_FREE, 0x7e);
        }
        __syncwarp();
        asm volatile("ld.relaxed.gpu.global.u32 %0, [%1];" : "=r"(tag0) : "l"(&g_s.epoch) : "memory");
        uint32_t x01, x23;
        {
            const uint32_t* xp = reinterpret_cast<const uint32_t*>(p.x + wqu * 64 + ((lane >> 2) & 3) * 16 + (lane & 3) * 2);
            asm volatile("ld.global.u32 %0, [%1];" : "=r"(x01) : "l"(xp) : "memory");
            asm volatile("ld.global.u32 %0, [%1];" : "=r"(x23) : "l"(xp + 4) : "memory");
        }
        __syncthreads();
        TS(44);
        const uint32_t koff = k_offset(slots, wj, lane), voff = v_offset(slots, wj, lane);
#pragma unroll
        for (int r = 0; r < 3; r++) {
            const int sk = 2 + 2 * r, sv = (r == 2) ? 1 : sk + 1;
            mbar_wait(bars + sk * 8, 0);
            if (wj == 0 && lane == 0) issue_item(2 * r + PD, tm, tb, ui, hasX, slots, bars);
            __syncwarp();
            load_kfrag(rk[r], koff + sk * SLOT);
            mbar_wait(bars + sv * 8, 0);
            if (wj == 0 && lane == 0) issue_item(2 * r + 1 + PD, tm, tb, ui, hasX, slots, bars);
            __syncwarp();
#pragma unroll
            for (int kk = 0; kk < 4; kk++)
#pragma unroll
                for (int mt = 0; mt < 2; mt++) ldsm4t(rv[r] + kk * 8 + mt * 4, sv * SLOT + kk * 2048 + (voff ^ (mt << 5)));
            wg_bar_or(barid, false);
            if (r == 0) tag0 = tag0 * 4 + 1;
            if (r == QAT && worker) {
                if (wqu == (cta >> 4) && lane == (cta & 15)) sts64(SM_XR, x01, x23);
                q_stage<0>(p, cta, tag0, x01, x23);
            }
        }
        if (lane == 0) {
            if (wj == 0) ticket = draw_ticket(p, cta, 0);
            if (wqu == 5 && cta < 112) tma_rows(&tm.wd, cta * 16, slots + 6 * SLOT, bars + 6 * 8);
        }
        __syncwarp();
        gather_q<0>(p, cta, head, qbase, tag0, barid);
        PACE();
        float s[3][4];
#pragma unroll
        for (int r = 0; r < 3; r++) qk_regs(s[r], rk[r], Q_RD);
        first_max<3>(s, acc, mx, barid, lane, wj);
#pragma unroll
        for (int r = 0; r < 3; r++) {
            const uint2 pf = p_frag(s[r], acc);
            if (lane < 16) sts64(P_WR, pf.x, pf.y);
            wg_bar_or(barid, false);
            pv_regs(acc, rv[r], P_RD);
            wg_bar_or(barid, false);
        }
        nx = DESC(2, 3, 1, 1);
    }

    attention_pass<0>(tm, p, cta, tag0, acc, nx, ticket);
    {
        uint32_t rx[32];
        {
        UVARS
        (void)rec; (void)mx; (void)qbase; (void)tb; (void)ui; (void)bars;
        const int lane = tid_now() & 31;
        load_kfrag(rx, k_offset(slots, wj, lane));
        wg_bar_or(barid, false);
        if (worker && lane == 0) {
            const int u = cta * 2 + wg;
            if (wj == 3) tma_rows(&tm.wo, cta * 32 + wg * 16, slots, SM_WBAR);
            if ((WPF & 4) && (wj == 1 || wj == 2)) l2_prefetch((wj == 1 ? p.wg : p.wu) + (size_t)u * 7168, 7168, pol_first());
            if ((WPF & 16) && wj == 1) l2_prefetch(p.wq + (size_t)u * 16384, 16384, pol_first());
        }
        }
        __syncwarp();
        if (worker) {
            prewrite(p, cta, tag0);
            gemv_chain<false>(tm, p, cta, tag0 + 1);
            q_stage<1>(p, cta, tag0 + 1);
        }
        UVARS
        gather_q<1>(p, cta, head, qbase, tag0 + 1, barid);
        const int lane = tid_now() & 31;
        int nk = __shfl_sync(0xffffffffu, lds32(rec + 8), 0) & 255;
        const bool haveL = nk > 0;
        if (haveL) nk--;
        const bool keep0 = NKFIRST > 0 && nk > 0, keep1 = NKFIRST > 1 && nk > 1;
        if (wj == 1 && lane == 0) { tma_tile(&tm.k, tb + T_DYN0 + ui, slots, bars); TT(1, head, T_DYN0 + ui); }
        __syncwarp();
        float s[6][4];
        qk_regs(s[0], rx, Q_RD);
        {
            const uint32_t koff = k_offset(slots, wj, lane);
            qk_smem(s[1], koff + 2 * SLOT, Q_RD);
            qk_smem(s[2], koff + 4 * SLOT, Q_RD);
        }
        wg_bar_or(barid, false);
        ticket = 0;
        if (lane == 0) {
            if (wj == 0) {
                ticket = draw_ticket(p, cta, 1);
                const uint32_t d1 = DESC(0, 2, 1, 1) | 256, d2 = DESC(3, 5, 1, 1);
                sts32(rec + 4, keep0 ? (keep1 ? (d2 | d1 << 10) : d1) : 0);
                sts32(rec + 8, nk | (keep1 ? 2 << 8 : (keep0 ? 1 << 8 : 0) | S_FREE) | S_STREAM);
            }
            if (wj == 1) tma_tile(&tm.v, tb + T_DYN0 + ui, slots + 2 * SLOT, bars + 2 * 8);
            if (wj == 2 && keep0) tma_tile(&tm.k, tb + lds16(SM_KEEP + wg * 64), slots + 4 * SLOT, bars + 4 * 8);
        }
        __syncwarp();
        TS(11);
#pragma unroll
        for (int r = 0; r < 3; r++) qk_regs(s[3 + r], rk[r], Q_RD);
        if (!haveL) s[0][0] = s[0][1] = s[0][2] = s[0][3] = __int_as_float(0xff800000);
        first_max<6>(s, acc, mx, barid, lane, wj);
        {
            const uint32_t voff = v_offset(slots, wj, lane);
#pragma unroll
            for (int r = 0; r < 3; r++) {
                const uint32_t vb = voff + (1 + 2 * r) * SLOT;
                const uint2 pf = p_frag(s[r], acc);
                if (lane < 16) sts64(P_WR, pf.x, pf.y);
                uint32_t f[16];
                load_vpre(f, vb);
                wg_bar_or(barid, false);
                if (r > 0 || haveL) pv_smem(acc, f, vb, P_RD);
                wg_bar_or(barid, false);
                if (lane == 0 && wj == 1 + r) {
                    if (r == 0 && keep0) tma_tile(&tm.v, tb + lds16(SM_KEEP + wg * 64), slots + SLOT, bars + 8);
                    if (r == 1 && keep1) tma_tile(&tm.k, tb + lds16(SM_KEEP + wg * 64 + 2), slots + 3 * SLOT, bars + 3 * 8);
                    if (r == 2 && keep1) tma_tile(&tm.v, tb + lds16(SM_KEEP + wg * 64 + 2), slots + 5 * SLOT, bars + 5 * 8);
                }
                __syncwarp();
            }
        }
        TS(12);
#pragma unroll
        for (int r = 0; r < 3; r++) {
            const uint2 pf = p_frag(s[3 + r], acc);
            if (lane < 16) sts64(P_WR, pf.x, pf.y);
            wg_bar_or(barid, false);
            pv_regs(acc, rv[r], P_RD);
            wg_bar_or(barid, false);
        }
        TS(13);
        nx = keep0 ? DESC(4, 1, 1, 1) : (DESC(0, 2, 1, 1) | 256);
    }
    attention_pass<1>(tm, p, cta, tag0, acc, nx, ticket);
    __syncwarp();
    if (worker) gemv_chain<true>(tm, p, cta, tag0 + 2);
}

typedef CUresult (*EncodeFn)(CUtensorMap*, CUtensorMapDataType, cuuint32_t, void*, const cuuint64_t*, const cuuint64_t*,
                             const cuuint32_t*, const cuuint32_t*, CUtensorMapInterleave, CUtensorMapSwizzle,
                             CUtensorMapL2promotion, CUtensorMapFloatOOBfill);

void make_map(EncodeFn encode, CUtensorMap* m, void* base, int rank, const cuuint64_t* gd, const cuuint64_t* gs,
              const cuuint32_t* bx, CUtensorMapSwizzle sw) {
    const cuuint32_t es[3] = {1, 1, 1};
    encode(m, CU_TENSOR_MAP_DATA_TYPE_BFLOAT16, rank, base, gd, gs, bx, es, CU_TENSOR_MAP_INTERLEAVE_NONE, sw,
           CU_TENSOR_MAP_L2_PROMOTION_NONE, CU_TENSOR_MAP_FLOAT_OOB_FILL_NONE);
}

}

extern "C" void kernel_launch(void* const* d_in, const int* in_sizes, int n_in, void* d_out, int out_size) {
    (void)in_sizes; (void)n_in; (void)out_size;
    static EncodeFn encode = nullptr;
    static void* scratch = nullptr;
    if (!encode) {
        void* fn = nullptr;
        cudaDriverEntryPointQueryResult qr;
        cudaGetDriverEntryPoint("cuTensorMapEncodeTiled", &fn, cudaEnableDefault, &qr);
        encode = (EncodeFn)fn;
        cudaGetSymbolAddress(&scratch, g_scratch);
        cudaFuncSetAttribute(fused_kernel, cudaFuncAttributeMaxDynamicSharedMemorySize, SM_TOTAL);
    }
    Maps tm;
    {
        const cuuint64_t gd[3] = {64, 8ull * 65536ull, 2}, gs[2] = {256, 128};
        const cuuint32_t bx[3] = {64, 64, 2};
        make_map(encode, &tm.k, d_in[1], 3, gd, gs, bx, CU_TENSOR_MAP_SWIZZLE_128B);
        make_map(encode, &tm.v, d_in[2], 3, gd, gs, bx, CU_TENSOR_MAP_SWIZZLE_128B);
    }
    {
        const cuuint64_t gd[2] = {4096, 512}, gs[1] = {8192};
        const cuuint32_t bx[2] = {32, 256};
        make_map(encode, &tm.wq, d_in[3], 2, gd, gs, bx, CU_TENSOR_MAP_SWIZZLE_64B);
    }
    {
        const cuuint64_t gd[3] = {64, 4096, 8}, gs[2] = {1024, 128};
        const cuuint32_t bx[3] = {64, 16, 8};
        make_map(encode, &tm.wo, d_in[4], 3, gd, gs, bx, CU_TENSOR_MAP_SWIZZLE_128B);
        const cuuint64_t gd2[3] = {64, 1792, 8};
        make_map(encode, &tm.wd, d_in[8], 3, gd2, gs, bx, CU_TENSOR_MAP_SWIZZLE_128B);
    }
    {
        const cuuint64_t gd[2] = {1792, 512}, gs[1] = {3584};
        const cuuint32_t bx[2] = {16, 256};
        make_map(encode, &tm.wg, d_in[6], 2, gd, gs, bx, CU_TENSOR_MAP_SWIZZLE_32B);
        make_map(encode, &tm.wu, d_in[7], 2, gd, gs, bx, CU_TENSOR_MAP_SWIZZLE_32B);
    }
    Params p;
    p.x = (const __nv_bfloat16*)d_in[0];
    p.k = (const char*)d_in[1];
    p.v = (const char*)d_in[2];
    p.wq = (const char*)d_in[3];
    p.wo = (const char*)d_in[4];
    p.wg = (const char*)d_in[6];
    p.wu = (const char*)d_in[7];
    p.wd = (const char*)d_in[8];
    p.out = (__nv_bfloat16*)d_out;
    p.s = (Scratch*)scratch;
    fused_kernel<<<NCTA, 256, SM_TOTAL, cudaStreamPerThread>>>(tm, p);
}
```

```cpp
#include <cuda_runtime.h>
#include <cuda_bf16.h>
#include <cuda.h>
#include <stdint.h>

namespace {

constexpr int NCTA      = 132;
constexpr int NUNIT     = 33;
constexpr int NTILE     = 1024;
constexpr int SLOT      = 16384;
constexpr int NSTAT     = 7;
constexpr int T_DYN0    = NSTAT * NUNIT;
#define NKEEP 198
#define KEEP_TAILSKIP 33
#define KRATIO 1
#define D_AR 650
#define D_SKIP 1500
#define WQ_EARLY 1
#define D_AG 200
#define PF_REM 0
#define RUNROLL 1
#define SUNROLL 1
#define MID_NPRE 2
#define S1_NPRE 2
#define MID_DPRE 0
#define ECAP 24
#define DBG_U 0
#define DBG_PH 0
constexpr int T_KEEP0   = NTILE - NKEEP;
constexpr int T_KEEPEND = NTILE - KEEP_TAILSKIP;
constexpr int SUNR      = SUNROLL, RUNR = RUNROLL;
constexpr int KEEPCAP   = 32;
constexpr unsigned SPIN_LIMIT = 1u << 22;

constexpr uint32_t SM_BASE  = 1024;
constexpr uint32_t USTR     = 2 * SLOT + 3 * 24576;
constexpr uint32_t SM_SLOTS = SM_BASE;
constexpr uint32_t SM_WG    = SM_SLOTS + 2 * USTR;
constexpr uint32_t SM_Q     = SM_WG + SLOT;
constexpr uint32_t SM_P     = SM_Q + 1024;
constexpr uint32_t SM_RED   = SM_P + 1024;
constexpr uint32_t SM_MX    = SM_RED;
constexpr uint32_t SM_BAR   = SM_RED + 192;
constexpr uint32_t SM_WBAR  = SM_BAR + 96;
constexpr uint32_t SM_TBAR  = SM_BAR + 104;
constexpr uint32_t SM_DBAR  = SM_BAR + 112;
constexpr uint32_t SM_KEEP  = SM_BAR + 128;
constexpr uint32_t SM_ST    = SM_KEEP + 128;
constexpr uint32_t SM_CMP   = SM_ST + 32;
constexpr uint32_t SM_ESC   = SM_CMP + 64;
constexpr int SM_TOTAL      = SM_ESC + 2 * ECAP * 8 - SM_BASE;
static_assert(SM_TOTAL <= 232448 && ECAP <= 32, "smem");

struct Scratch {
    uint4 part[128][8][NUNIT][2];
    uint4 ar[4][2][128][8];
    uint2 x2[256];
    uint4 q[2][2][8][128];
    unsigned ticket[2][8][32];
    unsigned done[32];
    unsigned epoch;
};
__device__ Scratch g_scratch;
#define g_s (*p.s)
#define TS(i)
#define TSD(i)
#define TSW(i)
#define TT(ph, head, tile)

struct Maps { CUtensorMap k, v, wq, wo, wg, wu, wd; };
struct Params {
    const __nv_bfloat16* x;
    const char* k;
    const char* v;
    const char* wq;
    const char* wo;
    const char* wg;
    const char* wu;
    const char* wd;
    __nv_bfloat16* out;
    Scratch* s;
};

__device__ __forceinline__ void mbar_init(uint32_t bar, uint32_t cnt) {
    asm volatile("{\n.reg .pred p;\nelect.sync _|p, 0xffffffff;\n@p mbarrier.init.shared::cta.b64 [%0], %1;\n}" ::"r"(bar), "r"(cnt) : "memory");
}
__device__ __forceinline__ void mbar_wait(uint32_t bar, uint32_t parity) {
    asm volatile("{\n.reg .pred p, q;\n.reg .u32 c;\n"
                 "mbarrier.try_wait.parity.shared::cta.b64 p, [%0], %1;\n@p bra D_%=;\nmov.u32 c, 0;\n"
                 "W_%=:\nmbarrier.try_wait.parity.shared::cta.b64 p, [%0], %1;\nadd.u32 c, c, 1;\n"
                 "setp.lt.and.u32 q, c, %2, !p;\n@q bra W_%=;\n@!p trap;\nD_%=:\n}"
                 ::"r"(bar), "r"(parity), "n"(SPIN_LIMIT) : "memory");
}
__device__ __forceinline__ void spin_guard(uint32_t& it) {
    asm volatile("{\n.reg .pred q;\nadd.u32 %0, %0, 1;\nsetp.gt.u32 q, %0, %1;\n@q trap;\n}" : "+r"(it) : "n"(SPIN_LIMIT));
}
constexpr uint64_t POL_FIRST = 0x12f0000000000000ull, POL_NORMAL = 0x16f0000000000000ull;
__device__ __forceinline__ void tma_rows(const CUtensorMap* tm, int row, uint32_t dst, uint32_t bar) {
    asm volatile("{\n.reg .pred p;\nelect.sync _|p, 0xffffffff;\n"
                 "@p mbarrier.arrive.expect_tx.shared::cta.b64 _, [%4], %6;\n"
                 "@p cp.async.bulk.tensor.3d.shared::cluster.global.mbarrier::complete_tx::bytes.L2::cache_hint "
                 "[%0], [%1, {%2, %3, %2}], [%4], %5;\n}"
                 ::"r"(dst), "l"(tm), "r"(0), "r"(row), "r"(bar), "l"(POL_FIRST), "r"(SLOT) : "memory");
}
__device__ __forceinline__ void tma_tile(const CUtensorMap* tm, int gtile, uint32_t dst, uint32_t bar) {
    tma_rows(tm, gtile * 64, dst, bar);
}
__device__ __forceinline__ void expect_tx(uint32_t bar, uint32_t bytes) {
    asm volatile("{\n.reg .pred p;\nelect.sync _|p, 0xffffffff;\n@p mbarrier.arrive.expect_tx.shared::cta.b64 _, [%0], %1;\n}"
                 ::"r"(bar), "r"(bytes) : "memory");
}
__device__ __forceinline__ void tma_2d(const CUtensorMap* tm, int c0, int c1, uint32_t dst, uint32_t bar) {
    asm volatile("{\n.reg .pred p;\nelect.sync _|p, 0xffffffff;\n"
                 "@p cp.async.bulk.tensor.2d.shared::cluster.global.mbarrier::complete_tx::bytes.L2::cache_hint "
                 "[%0], [%1, {%2, %3}], [%4], %5;\n}"
                 ::"r"(dst), "l"(tm), "r"(c0), "r"(c1), "r"(bar), "l"(POL_FIRST) : "memory");
}
__device__ __forceinline__ void l2_prefetch(const void* p, uint32_t bytes, uint64_t pol) {
    asm volatile("{\n.reg .pred p;\nelect.sync _|p, 0xffffffff;\n"
                 "@p cp.async.bulk.prefetch.L2.global.L2::cache_hint [%0], %1, %2;\n}" ::"l"(p), "r"(bytes), "l"(pol) : "memory");
}
__device__ __forceinline__ void ldsm4(uint32_t* r, uint32_t a) {
    asm volatile("ldmatrix.sync.aligned.m8n8.x4.shared.b16 {%0,%1,%2,%3}, [%4];"
                 : "=r"(r[0]), "=r"(r[1]), "=r"(r[2]), "=r"(r[3]) : "r"(a) : "memory");
}
__device__ __forceinline__ void ldsm4t(uint32_t* r, uint32_t a) {
    asm volatile("ldmatrix.sync.aligned.m8n8.x4.trans.shared.b16 {%0,%1,%2,%3}, [%4];"
                 : "=r"(r[0]), "=r"(r[1]), "=r"(r[2]), "=r"(r[3]) : "r"(a) : "memory");
}
__device__ __forceinline__ void mma(float* c, const uint32_t* a, uint32_t b0, uint32_t b1) {
    asm volatile("mma.sync.aligned.m16n8k16.row.col.f32.bf16.bf16.f32 {%0,%1,%2,%3}, {%4,%5,%6,%7}, {%8,%9}, {%0,%1,%2,%3};"
                 : "+f"(c[0]), "+f"(c[1]), "+f"(c[2]), "+f"(c[3])
                 : "r"(a[0]), "r"(a[1]), "r"(a[2]), "r"(a[3]), "r"(b0), "r"(b1));
}
__device__ __forceinline__ uint32_t movm(uint32_t a) {
    uint32_t d; asm volatile("movmatrix.sync.aligned.m8n8.trans.b16 %0, %1;" : "=r"(d) : "r"(a)); return d;
}
__device__ __forceinline__ uint32_t pack_bf16(float lo, float hi) {
    uint32_t d; asm("cvt.rn.bf16x2.f32 %0, %1, %2;" : "=r"(d) : "f"(hi), "f"(lo)); return d;
}
__device__ __forceinline__ float bf16r(float v) { return __uint_as_float(pack_bf16(v, 0.f) << 16); }
__device__ __forceinline__ float bf_lo(uint32_t w) { return __uint_as_float(w << 16); }
__device__ __forceinline__ float bf_hi(uint32_t w) { return __uint_as_float(w & 0xffff0000u); }
__device__ __forceinline__ float ex2(float v) { float d; asm("ex2.approx.ftz.f32 %0, %1;" : "=f"(d) : "f"(v)); return d; }
__device__ __forceinline__ uint4 lds128(uint32_t a) {
    uint4 v; asm volatile("ld.shared.v4.u32 {%0,%1,%2,%3}, [%4];" : "=r"(v.x), "=r"(v.y), "=r"(v.z), "=r"(v.w) : "r"(a) : "memory"); return v;
}
__device__ __forceinline__ uint2 lds64(uint32_t a) {
    uint2 v; asm volatile("ld.shared.v2.u32 {%0,%1}, [%2];" : "=r"(v.x), "=r"(v.y) : "r"(a) : "memory"); return v;
}
__device__ __forceinline__ uint32_t lds32(uint32_t a) {
    uint32_t v; asm volatile("ld.shared.u32 %0, [%1];" : "=r"(v) : "r"(a) : "memory"); return v;
}
__device__ __forceinline__ void sts128(uint32_t a, uint32_t x, uint32_t y, uint32_t z, uint32_t w) {
    asm volatile("st.shared.v4.u32 [%0], {%1,%2,%3,%4};" ::"r"(a), "r"(x), "r"(y), "r"(z), "r"(w) : "memory");
}
__device__ __forceinline__ void sts64(uint32_t a, uint32_t x, uint32_t y) {
    asm volatile("st.shared.v2.u32 [%0], {%1,%2};" ::"r"(a), "r"(x), "r"(y) : "memory");
}
__device__ __forceinline__ void sts32(uint32_t a, uint32_t x) {
    asm volatile("st.shared.u32 [%0], %1;" ::"r"(a), "r"(x) : "memory");
}
__device__ __forceinline__ void sts16(uint32_t a, uint32_t x) {
    asm volatile("st.shared.u16 [%0], %1;" ::"r"(a), "h"((unsigned short)x) : "memory");
}
__device__ __forceinline__ uint32_t lds16(uint32_t a) {
    unsigned short v; asm volatile("ld.shared.u16 %0, [%1];" : "=h"(v) : "r"(a) : "memory"); return v;
}
__device__ __forceinline__ bool wg_bar_or(int id, bool p) {
    uint32_t r;
    asm volatile("{\n.reg .pred a, b;\nsetp.ne.u32 a, %2, 0;\nbar.red.or.pred b, %1, 128, a;\nselp.u32 %0, 1, 0, b;\n}"
                 : "=r"(r) : "r"(id), "r"((uint32_t)p) : "memory");
    return r != 0;
}
__device__ __forceinline__ uint4 ll_ld(const uint4* p) {
    unsigned long long a, b;
    asm volatile("ld.relaxed.gpu.global.v2.b64 {%0,%1}, [%2];" : "=l"(a), "=l"(b) : "l"(p) : "memory");
    return make_uint4((uint32_t)a, (uint32_t)(a >> 32), (uint32_t)b, (uint32_t)(b >> 32));
}
__device__ __forceinline__ void ll_st(uint4* p, uint32_t v0, uint32_t t0, uint32_t v1, uint32_t t1) {
    unsigned long long a = ((unsigned long long)t0 << 32) | v0, b = ((unsigned long long)t1 << 32) | v1;
    asm volatile("st.relaxed.gpu.global.v2.b64 [%0], {%1,%2};" ::"l"(p), "l"(a), "l"(b) : "memory");
}
__device__ __forceinline__ uint4 ll_ld_last(const uint4* p) {
    unsigned long long a, b;
    asm volatile("ld.relaxed.gpu.global.L2::cache_hint.v2.b64 {%0,%1}, [%2], %3;" : "=l"(a), "=l"(b) : "l"(p), "l"(POL_FIRST) : "memory");
    return make_uint4((uint32_t)a, (uint32_t)(a >> 32), (uint32_t)b, (uint32_t)(b >> 32));
}
__device__ __forceinline__ void bar_sync(int id, int n) { asm volatile("bar.sync %0, %1;" ::"r"(id), "r"(n) : "memory"); }
__device__ __forceinline__ void bar_arrive(int id, int n) { asm volatile("bar.arrive %0, %1;" ::"r"(id), "r"(n) : "memory"); }
__device__ __forceinline__ void delay_cycles(int n) {
    if (n > 0) {
        uint32_t t0, t1;
        asm volatile("mov.u32 %0, %%clock;" : "=r"(t0));
        do { asm volatile("mov.u32 %0, %%clock;" : "=r"(t1)); } while (t1 - t0 < (uint32_t)n);
    }
}
__device__ __forceinline__ int tid_now() {
    int t; asm volatile("mov.u32 %0, %%tid.x;" : "=r"(t)); return t;
}
__device__ __forceinline__ bool mbar_test(uint32_t bar, uint32_t parity) {
    uint32_t ok;
    asm volatile("{\n.reg .pred p;\nmbarrier.test_wait.parity.shared::cta.b64 p, [%1], %2;\nselp.u32 %0, 1, 0, p;\n}"
                 : "=r"(ok) : "r"(bar), "r"(parity) : "memory");
    return ok != 0;
}

struct Acc {
    float o[2][4];
    float l[4];
    float m0, m1;
};

constexpr float SCALE_LOG2 = 0.08838834764831845f * 1.4426950408889634f;

__device__ __forceinline__ void softmax_step(float* s, Acc& a, uint32_t p_wr, uint32_t mx, int barid, int lane, int wj) {
#pragma unroll
    for (int i = 0; i < 4; i++) s[i] *= SCALE_LOG2;
    bool over = fmaxf(s[0], s[2]) > a.m0 || fmaxf(s[1], s[3]) > a.m1;
    {
        uint32_t b0 = movm(pack_bf16(ex2(s[0] - a.m0), ex2(s[1] - a.m1)));
        uint32_t b1 = movm(pack_bf16(ex2(s[2] - a.m0), ex2(s[3] - a.m1)));
        if (lane < 16) sts64(p_wr, b0, b1);
    }
    if (wg_bar_or(barid, over)) {
        float x0 = fmaxf(s[0], s[2]), x1 = fmaxf(s[1], s[3]);
#pragma unroll
        for (int d = 4; d < 32; d <<= 1) {
            x0 = fmaxf(x0, __shfl_xor_sync(0xffffffffu, x0, d));
            x1 = fmaxf(x1, __shfl_xor_sync(0xffffffffu, x1, d));
        }
        if (lane < 2) sts64(mx + wj * 16 + lane * 8, __float_as_uint(x0), __float_as_uint(x1));
        wg_bar_or(barid, false);
        float n0 = a.m0, n1 = a.m1;
#pragma unroll
        for (int j = 0; j < 4; j++) {
            uint2 v = lds64(mx + j * 16 + (lane & 1) * 8);
            n0 = fmaxf(n0, __uint_as_float(v.x));
            n1 = fmaxf(n1, __uint_as_float(v.y));
        }
        float f0 = ex2(a.m0 - n0), f1 = ex2(a.m1 - n1);
        a.m0 = n0; a.m1 = n1;
        a.o[0][0] *= f0; a.o[0][2] *= f0; a.o[1][0] *= f0; a.o[1][2] *= f0; a.l[0] *= f0; a.l[2] *= f0;
        a.o[0][1] *= f1; a.o[0][3] *= f1; a.o[1][1] *= f1; a.o[1][3] *= f1; a.l[1] *= f1; a.l[3] *= f1;
        uint32_t b0 = movm(pack_bf16(ex2(s[0] - n0), ex2(s[1] - n1)));
        uint32_t b1 = movm(pack_bf16(ex2(s[2] - n0), ex2(s[3] - n1)));
        if (lane < 16) sts64(p_wr, b0, b1);
        wg_bar_or(barid, false);
    }
}

struct Pack {
    uint32_t cmp;
    uint32_t esc;
    uint32_t key;
};
__device__ __forceinline__ void pack16(const uint32_t* a, uint32_t b4, uint32_t d0, uint32_t d1, uint32_t d2, int it,
                                       const Pack& pk) {
    uint32_t x0[4], x1[4], n[4];
#pragma unroll
    for (int g = 0; g < 4; g++) {
        x0[g] = __byte_perm(a[4 * g], a[4 * g + 1], 0x7531) - b4;
        x1[g] = __byte_perm(a[4 * g + 2], a[4 * g + 3], 0x7531) - b4;
    }
    sts128(d0, __byte_perm(a[0], a[1], 0x6420), __byte_perm(a[2], a[3], 0x6420),
               __byte_perm(a[4], a[5], 0x6420), __byte_perm(a[6], a[7], 0x6420));
    sts128(d1, __byte_perm(a[8], a[9], 0x6420), __byte_perm(a[10], a[11], 0x6420),
               __byte_perm(a[12], a[13], 0x6420), __byte_perm(a[14], a[15], 0x6420));
#pragma unroll
    for (int g = 0; g < 4; g++) n[g] = x0[g] | __funnelshift_l(x1[g], x1[g], 4);
    if ((x0[0] | x1[0] | x0[1] | x1[1] | x0[2] | x1[2] | x0[3] | x1[3]) & 0x78787878u) {
        asm volatile("red.shared.or.b32 [%0], %1;" ::"r"(pk.cmp + 16 + ((pk.key >> 3) & 12)),
                     "r"(1u << ((pk.key >> 11) * 4 + it)) : "memory");
#pragma unroll
        for (int g = 0; g < 4; g++) {
            const bool bad = ((x0[g] | x1[g]) & 0x78787878u) != 0;
            asm volatile("{\n.reg .pred p;\n.reg .u32 i;\nsetp.ne.u32 p, %0, 0;\nmov.u32 i, %5;\n"
                         "@p atom.shared.inc.u32 i, [%1], 0xfffffffe;\nsetp.lt.u32 p, i, %5;\nmad.lo.u32 i, i, 8, %2;\n"
                         "@p st.shared.v2.u32 [i], {%3, %4};\n}"
                         ::"r"((uint32_t)bad), "r"(pk.cmp + 8), "r"(pk.esc), "r"(pk.key | it << 9 | g << 7), "r"(x1[g] + b4),
                           "n"(ECAP) : "memory");
            if (bad) n[g] = x0[g] + b4;
        }
    }
    __syncwarp();
    sts128(d2, n[0], n[1], n[2], n[3]);
}
__device__ __forceinline__ void unpack16(uint32_t* a, uint32_t b4, uint32_t c, int it, uint32_t flags, const Pack& pk) {
    const uint4 nn = lds128(c + 4096);
    const uint4 l0 = lds128(c), l1 = lds128(c + 2048);
    const uint32_t n[4] = {nn.x, nn.y, nn.z, nn.w};
    uint32_t h0[4], h1[4];
#pragma unroll
    for (int g = 0; g < 4; g++) {
        h0[g] = (n[g] & 0x87878787u) + b4;
        h1[g] = (__funnelshift_r(n[g], n[g], 4) & 0x87878787u) + b4;
    }
    if (flags >> it & 1) {
        const uint32_t me = pk.key | it << 9;
        const uint2 e = lds64(pk.esc + min(me & 31u, ECAP - 1u) * 8);
        uint32_t hit = __ballot_sync(0xffffffffu, ((e.x ^ me) & ~0x19fu) == 0) & (uint32_t)((1ull << ECAP) - 1);
#pragma unroll 1
        while (hit) {
            const int src = __ffs(hit) - 1;
            hit &= hit - 1;
            const uint32_t d = __shfl_sync(0xffffffffu, e.x, src) ^ me, v = __shfl_sync(0xffffffffu, e.y, src);
#pragma unroll
            for (int g = 0; g < 4; g++)
                if (d == (uint32_t)(g << 7)) { h0[g] = n[g]; h1[g] = v; }
        }
    }
    const uint32_t l[8] = {l0.x, l0.y, l0.z, l0.w, l1.x, l1.y, l1.z, l1.w};
#pragma unroll
    for (int g = 0; g < 4; g++) {
        a[4 * g]     = __byte_perm(l[2 * g], h0[g], 0x5140);
        a[4 * g + 1] = __byte_perm(l[2 * g], h0[g], 0x7362);
        a[4 * g + 2] = __byte_perm(l[2 * g + 1], h1[g], 0x5140);
        a[4 * g + 3] = __byte_perm(l[2 * g + 1], h1[g], 0x7362);
    }
}

__device__ __forceinline__ void qk_half(float* s, float* s2, const uint32_t* a, uint32_t q) {
    const uint4 q0 = lds128(q), q1 = lds128(q + 256);
    mma(s, a, q0.x, q0.y);
    mma(s2, a + 4, q0.z, q0.w);
    mma(s, a + 8, q1.x, q1.y);
    mma(s2, a + 12, q1.z, q1.w);
}
__device__ __forceinline__ void pv_half(Acc& a, const uint32_t* f, uint32_t pa) {
    const uint32_t ones[4] = {0x3f803f80u, 0x3f803f80u, 0x3f803f80u, 0x3f803f80u};
    const uint4 pp = lds128(pa);
    mma(a.o[0], f, pp.x, pp.y);
    mma(a.o[1], f + 4, pp.x, pp.y);
    mma(a.l, ones, pp.x, pp.y);
    mma(a.o[0], f + 8, pp.z, pp.w);
    mma(a.o[1], f + 12, pp.z, pp.w);
    mma(a.l, ones, pp.z, pp.w);
}
__device__ __forceinline__ void load_khalf(uint32_t* a, uint32_t k) {
#pragma unroll
    for (int j = 0; j < 4; j++) ldsm4(a + j * 4, k ^ (j << 5));
    __syncwarp();
}
__device__ __forceinline__ void load_vhalf(uint32_t* f, uint32_t v) {
    ldsm4t(f, v);
    ldsm4t(f + 4, v ^ 32);
    ldsm4t(f + 8, v + 2048);
    ldsm4t(f + 12, (v ^ 32) + 2048);
    __syncwarp();
}
__device__ __forceinline__ void park(uint32_t* r, uint32_t kb, uint32_t vb) {
#pragma unroll
    for (int j = 0; j < 12; j++) {
        const int it = j / 3, c = j % 3;
        const uint32_t ad = it < 2 ? (kb ^ (c << 5)) + it * 8192 : (vb ^ ((c & 1) << 5)) + (c >> 1) * 2048 + (it - 2) * 4096;
        const uint4 u = lds128(ad);
        r[4 * j] = u.x; r[4 * j + 1] = u.y; r[4 * j + 2] = u.z; r[4 * j + 3] = u.w;
    }
}
__device__ __forceinline__ void unpark(const uint32_t* r, uint32_t c) {
#pragma unroll
    for (int j = 0; j < 12; j++) sts128(c + j * 2048, r[4 * j], r[4 * j + 1], r[4 * j + 2], r[4 * j + 3]);
}
__device__ __forceinline__ uint32_t k_offset(uint32_t slots, int wj, int lane) {
    const int row = wj * 16 + (lane & 7) + ((lane >> 3) & 1) * 8;
    return slots + row * 128 + (((lane >> 4) ^ (row & 7)) << 4);
}
__device__ __forceinline__ uint32_t v_offset(uint32_t slots, int wj, int lane) {
    const int key = (lane & 7) + (lane >> 4) * 8, cg = wj * 4 + ((lane >> 3) & 1);
    return slots + (cg >> 3) * 8192 + key * 128 + (((cg & 7) ^ (key & 7)) << 4);
}
__device__ __forceinline__ void load_kfrag(uint32_t* rk, uint32_t kb) {
#pragma unroll
    for (int ks = 0; ks < 8; ks++) ldsm4(rk + ks * 4, (kb ^ ((ks & 3) << 5)) + (ks >> 2) * 8192);
}

template <int NPRE>
__device__ __forceinline__ void ln_gemv_part(uint32_t (*f)[8], uint32_t a0, uint32_t a1, uint32_t kstride, uint32_t xw,
                                             int wq, int lane) {
    const int t = lane & 3, g = lane >> 2;
    float c0[4] = {0.f, 0.f, 0.f, 0.f}, c1[4] = {0.f, 0.f, 0.f, 0.f};
#pragma unroll
    for (int ks = 0; ks < 4; ks++) {
        uint32_t* ff = f[ks % NPRE];
        if (ks >= NPRE) {
            ldsm4t(ff, a0 + ks * kstride);
            ldsm4t(ff + 4, a1 + ks * kstride);
        }
        uint32_t xa = __shfl_sync(0xffffffffu, xw, ks * 8 + t), xb = __shfl_sync(0xffffffffu, xw, ks * 8 + 4 + t);
        if (g & 1) xa = xb = 0x3f803f80u;
        mma(c0, ff, xa, xb);
        mma(c1, ff + 4, xa, xb);
    }
    {
        const float a = bf_lo(xw), b = bf_hi(xw);
        const float su = a + b, sq = fmaf(a, a, b * b);
        float keep = (lane & 16) ? sq : su, send = (lane & 16) ? su : sq;
        keep += __shfl_xor_sync(0xffffffffu, send, 16);
#pragma unroll
        for (int k = 8; k > 0; k >>= 1) keep += __shfl_xor_sync(0xffffffffu, keep, k);
        if ((lane & 15) == 0) sts32(SM_RED + (lane >> 4) * 32 + wq * 4, __float_as_uint(keep));
    }
    float y = (t & 2) ? ((t & 1) ? c1[2] : c1[0]) : ((t & 1) ? c0[2] : c0[0]);
    float z = (t & 2) ? ((t & 1) ? c1[3] : c1[1]) : ((t & 1) ? c0[3] : c0[1]);
    sts64(SM_Q + wq * 256 + (t * 8 + g) * 8, __float_as_uint(y), __float_as_uint(z));
}
__device__ __forceinline__ float sum4(uint4 u) {
    return (__uint_as_float(u.x) + __uint_as_float(u.y)) + (__uint_as_float(u.z) + __uint_as_float(u.w));
}
__device__ __forceinline__ float ln_gemv_fin(int lane) {
    float mean, rstd;
    {
        const uint4 a = lds128(SM_RED), b = lds128(SM_RED + 16), c = lds128(SM_RED + 32), d = lds128(SM_RED + 48);
        mean = (sum4(a) + sum4(b)) * (1.f / 512.f);
        const float var = fmaxf(fmaf(sum4(c) + sum4(d), 1.f / 512.f, -mean * mean), 0.f) + 1e-5f;
        asm("rsqrt.approx.ftz.f32 %0, %1;" : "=f"(rstd) : "f"(var));
    }
    uint2 u[8];
#pragma unroll
    for (int j = 0; j < 8; j++) u[j] = lds64(SM_Q + j * 256 + lane * 8);
#define S8(f) (((__uint_as_float(u[0].f) + __uint_as_float(u[1].f)) + (__uint_as_float(u[2].f) + __uint_as_float(u[3].f))) + \
               ((__uint_as_float(u[4].f) + __uint_as_float(u[5].f)) + (__uint_as_float(u[6].f) + __uint_as_float(u[7].f))))
    return (S8(x) - mean * S8(y)) * rstd;
#undef S8
}
__device__ __forceinline__ void ar_add(uint4* dst, float y0, float y1) {
    asm volatile("red.relaxed.gpu.global.add.v4.f32 [%0], {%1, %2, %3, %1};" ::"l"(dst), "f"(1.f), "f"(y0), "f"(y1) : "memory");
}

__device__ __forceinline__ int unit_head(int cta, int wg) { return cta < 128 ? ((cta + (cta >> 3)) & 7) : (cta - 128) * 2 + wg; }
__device__ __forceinline__ int unit_index(int cta, int wg) { return cta < 128 ? (cta >> 3) * 2 + wg : 32; }
__device__ __forceinline__ void issue_item(int j, const Maps& tm, int tb, int ui, uint32_t slots, uint32_t bars) {
    const int slot = (int)((0x1010210432105432ull >> (4 * j)) & 15);
    tma_tile((j & 1) ? &tm.v : &tm.k, tb + (j >> 1) * NUNIT + ui, slots + slot * SLOT, bars + slot * 8);
}
__device__ __forceinline__ void load_ffn(const Maps& tm, int cta, int h, uint32_t z) {
    if (h) {
        tma_rows(&tm.wd, cta * 16, z, SM_WBAR);
    } else {
        expect_tx(SM_WBAR, SLOT);
        tma_2d(&tm.wu, cta * 16, 0, z, SM_WBAR);
        tma_2d(&tm.wu, cta * 16, 256, z + 8192, SM_WBAR);
    }
}
__device__ __forceinline__ void load_wq(const Maps& tm, int cta, int h, uint32_t z) {
    expect_tx(SM_WBAR, SLOT);
    tma_2d(&tm.wq, cta * 32, h * 256, z, SM_WBAR);
}
__device__ __forceinline__ void draw_ticket(uint32_t& ticket, const Params& p, int ph, int head, int lane) {
    asm volatile("{\n.reg .pred p;\nsetp.eq.u32 p, %2, 0;\n@p atom.relaxed.gpu.global.inc.u32 %0, [%1], 0xfffffffe;\n}"
                 : "+r"(ticket) : "l"(&g_s.ticket[ph][head][0]), "r"(lane) : "memory");
}
#define DESC(sk, sv) ((uint32_t)((sk) | ((sv) << 3) | 64))

__device__ __forceinline__ uint4* part_dst(const Params& p, int head, int ui, int tid) {
    const int lane = tid & 31, g = lane >> 2, t = lane & 3;
    return &g_s.part[(head * 4 + 2 * (t & 1) + (t >> 1)) * 4 + ((tid >> 5) & 3)][g >> 1][ui][g & 1];
}
__device__ __forceinline__ uint4* q_dst(const Params& p, int layer, int cta, int lane) {
    return &g_s.q[layer][(lane >> 3) & 1][cta >> 4][((cta & 3) * 16 + ((cta >> 2) & 3) * 4) * 2 + (lane & 7)];
}
__device__ __forceinline__ void publish_q(uint4* out, float r, uint32_t tag, int lane) {
    const int src = (lane & 1) * 16 + ((lane >> 1) & 3) * 2;
    const float q0 = __shfl_sync(0xffffffffu, r, src), q1 = __shfl_sync(0xffffffffu, r, src + 1);
    const float q2 = __shfl_sync(0xffffffffu, r, src + 8), q3 = __shfl_sync(0xffffffffu, r, src + 9);
    if (lane < 16) ll_st(out, pack_bf16(q0, q1), tag, pack_bf16(q2, q3), tag);
}

template <bool TAIL>
__device__ __forceinline__ void gemv_chain(const Maps& tm, const Params& p, const int cta, const uint32_t tag) {
    constexpr uint32_t Z_WO = SM_SLOTS + (TAIL ? 2 : 0) * SLOT, Z_GU = SM_SLOTS + (TAIL ? 3 : 0) * SLOT;
    [[maybe_unused]] constexpr int TB = TAIL ? 16 : 0;
    const int wq = __shfl_sync(0xffffffffu, tid_now() >> 5, 0);
    uint32_t xo;
    {
        const int lane = tid_now() & 31, g = lane >> 2, t = lane & 3;
        if (!TAIL) {
            const unsigned short* xp = reinterpret_cast<const unsigned short*>(p.x) + wq * 64 + t * 16 + g;
            xo = xp[0] | (uint32_t)xp[8] << 16;
            if (wq == 0 && lane < 16) ll_st(q_dst(p, 1, cta, lane), 0, 0, 0, 0);
            __syncwarp();
            if (wq == 1) l2_prefetch(&g_s.ar[0][0][0][0] + (cta & 63) * 128, 2048, POL_NORMAL);
        } else {
            unsigned long long u;
            uint32_t it = 0;
            do {
                spin_guard(it);
                asm volatile("ld.relaxed.gpu.global.b64 %0, [%1];" : "=l"(u) : "l"(&g_s.x2[wq * 32 + lane]) : "memory");
            } while (__any_sync(0xffffffffu, (uint32_t)(u >> 32) != tag - 1));
            xo = (uint32_t)u;
        }
        const uint32_t t16 = tag & 0xffffu;
        const uint4* src = &g_s.part[cta][wq][lane & 15][lane >> 4];
        const bool three = (lane & 15) == 0;
        if (wq == 0) {
            const uint32_t target = ((tag >> 2) * 2 + (TAIL ? 2 : 1)) * (2 * NCTA);
            uint32_t it = 0;
            bool pf = !TAIL;
            while (true) {
                uint32_t v;
                asm volatile("ld.acquire.gpu.global.u32 %0, [%1];" : "=r"(v) : "l"(&g_s.done[0]) : "memory");
                const int rem = __shfl_sync(0xffffffffu, (int)(target - v), 0);
                if (pf && rem <= PF_REM) {
                    pf = false;
                    l2_prefetch(p.wu + (size_t)cta * 14336, 14336, POL_FIRST);
                    l2_prefetch(p.wd + (size_t)cta * 14336, 14336, POL_FIRST);
                }
                if (rem <= 0) break;
                spin_guard(it);
                if (rem > 16) delay_cycles(400);
            }
        }
        __syncthreads();
        TS(TB + 14);
        uint4 a = ll_ld_last(src), b = ll_ld_last(src + 32), e = make_uint4(0, 0xff800000u | t16, 0, t16);
        if (three) e = ll_ld_last(src + 64);
        const uint32_t wa0 = Z_WO + wq * 2048 + ((lane & 7) + (lane >> 4) * 8) * 128 + ((((lane >> 3) & 1) ^ (lane & 7)) << 4);
        uint32_t f0[4][4], f1[4][4];
        mbar_wait(TAIL ? SM_TBAR : SM_WBAR, TAIL ? 0 : 1);
        __syncwarp();
        if (TAIL) {
#pragma unroll
            for (int mt = 0; mt < 4; mt++) {
                ldsm4t(f0[mt], wa0 ^ (mt << 5));
                ldsm4t(f1[mt], (wa0 ^ (mt << 5)) + USTR);
            }
        }
        {
            uint32_t it = 0;
            while (__any_sync(0xffffffffu, ((a.y ^ t16) | (a.w ^ t16) | (b.y ^ t16) | (b.w ^ t16) | (e.y ^ t16) | (e.w ^ t16)) << 16 != 0)) {
                spin_guard(it);
                a = ll_ld_last(src);
                b = ll_ld_last(src + 32);
                if (three) e = ll_ld_last(src + 64);
            }
        }
        TS(TB + 0);
        if (!TAIL && wq >= 6) l2_prefetch(p.wq + (size_t)(cta + (wq - 6) * 128) * 16384, 16384, POL_FIRST);
        const float la = __uint_as_float(__byte_perm(a.w, a.y, 0x7632)), lb = __uint_as_float(__byte_perm(b.w, b.y, 0x7632));
        const float le = __uint_as_float(__byte_perm(e.w, e.y, 0x7632));
        float mm;
        {
            int k = __float_as_int(fmaxf(fmaxf(la, lb), le));
            k ^= (k >> 31) & 0x7fffffff;
            k = __reduce_max_sync(0xffffffffu, k);
            k ^= (k >> 31) & 0x7fffffff;
            mm = __int_as_float(k);
        }
        const float wa = ex2(la - mm), wb = ex2(lb - mm), we = ex2(le - mm);
        const float v0 = fmaf(we, __uint_as_float(e.x), fmaf(wb, __uint_as_float(b.x), wa * __uint_as_float(a.x)));
        const float v1 = fmaf(we, __uint_as_float(e.z), fmaf(wb, __uint_as_float(b.z), wa * __uint_as_float(a.z)));
        float ws = wa + wb + we;
        float kk = (lane & 8) ? v1 : v0;
        kk += __shfl_xor_sync(0xffffffffu, (lane & 8) ? v0 : v1, 8);
        ws += __shfl_xor_sync(0xffffffffu, ws, 8);
        if (!TAIL) {
#pragma unroll
            for (int mt = 0; mt < S1_NPRE; mt++) {
                ldsm4t(f0[mt], wa0 ^ (mt << 5));
                ldsm4t(f1[mt], (wa0 ^ (mt << 5)) + USTR);
            }
        }
#pragma unroll
        for (int k = 4; k > 0; k >>= 1) {
            kk += __shfl_xor_sync(0xffffffffu, kk, k);
            ws += __shfl_xor_sync(0xffffffffu, ws, k);
        }
        {
            float r; asm("rcp.approx.ftz.f32 %0, %1;" : "=f"(r) : "f"(ws));
            const uint32_t o = pack_bf16(kk * r, 0.f);
            if ((lane & 7) == 0) sts16(SM_RED + 128 + (wq & 3) * 16 + (wq >> 2) * 8 + ((lane >> 3) & 1) * 4 + (lane >> 4) * 2, o);
        }
        uint4* out = &g_s.ar[TAIL ? 2 : 0][cta & 1][wq * 16 + (lane >> 1)][lane & 1];
        __syncthreads();
        TS(TB + 1);
        const uint4 ob = lds128(SM_RED + 128 + t * 16);
        float c0[4] = {0.f, 0.f, 0.f, 0.f}, c1[4] = {0.f, 0.f, 0.f, 0.f};
#pragma unroll
        for (int mt = 0; mt < 4; mt++) {
            constexpr int NP = TAIL ? 4 : S1_NPRE;
            uint32_t* g0 = f0[mt % NP];
            uint32_t* g1 = f1[mt % NP];
            if (mt >= NP) {
                ldsm4t(g0, wa0 ^ (mt << 5));
                ldsm4t(g1, (wa0 ^ (mt << 5)) + USTR);
            }
            const bool mine = (g >> 1) == mt;
            mma(c0, g0, mine ? ob.x : 0u, mine ? ob.y : 0u);
            mma(c1, g1, mine ? ob.z : 0u, mine ? ob.w : 0u);
        }
        ar_add(out, c0[0] + c1[0], c0[2] + c1[2]);
        TS(TB + 2);
        if (!TAIL) {
            if (wq == 4 || wq == 5) bar_sync(4, 256); else bar_arrive(4, 256);
        }
    }
#pragma unroll 1
    for (int hv = 0; hv < 2; hv++) {
        const int half = __shfl_sync(0xffffffffu, hv, 0);
        const bool ffn = cta < 112;
        if (TAIL && (half ? cta != 0 : !ffn)) break;
        uint32_t t0;
        asm volatile("mov.u32 %0, %%clock;" : "=r"(t0));
        const int lane = tid_now() & 31, g = lane >> 2, t = lane & 3;
        const bool qs = !TAIL && half;
        [[maybe_unused]] const int h = wq - 4;
        [[maybe_unused]] const uint32_t z = SM_SLOTS + h * USTR;
        if (!TAIL && (wq == 4 || wq == 5)) {
            if (!half) {
                if (ffn) load_ffn(tm, cta, h, z);
            } else if (!(WQ_EARLY && ffn && h == 0)) {
                if (!ffn) delay_cycles(D_SKIP);
                load_wq(tm, cta, h, z);
            }
        }
        constexpr int NPRE = TAIL ? 4 : MID_NPRE;
        uint32_t f[NPRE][8];
        const int row = (wq & 3) * 64 + (lane & 7) + (lane >> 4) * 8;
        const uint32_t a0 = qs ? SM_SLOTS + (wq >> 2) * USTR + row * 64 + ((((lane >> 3) & 1) ^ ((lane >> 1) & 3)) << 4)
                               : SM_WG + (wq >> 2) * 8192 + row * 32 + ((((lane >> 3) ^ (lane >> 2)) & 1) << 4);
        const uint32_t a1 = qs ? a0 ^ 32 : a0 - (SM_WG - Z_GU), kstride = qs ? 1024 : 512;
        {
            const uint4* src = &g_s.ar[(TAIL ? 2 : 0) + half][0][wq * 16 + (lane >> 1)][lane & 1];
            const uint32_t cnt = __float_as_uint(half ? 56.f : 64.f);
            if (TAIL && !half) {
                mbar_wait(SM_WBAR, 0);
                __syncwarp();
#pragma unroll
                for (int ks = 0; ks < NPRE; ks++) {
                    ldsm4t(f[ks], a0 + ks * kstride);
                    ldsm4t(f[ks] + 4, a1 + ks * kstride);
                }
            }
            {
                const uint32_t d = (half && !ffn) ? D_AR + D_SKIP : D_AR;
                uint32_t t1;
                do { asm volatile("mov.u32 %0, %%clock;" : "=r"(t1)); } while (t1 - t0 < d);
            }
            uint4 u, v;
            uint32_t it = 0;
            do {
                spin_guard(it);
                u = ll_ld(src);
                v = ll_ld(src + 1024);
            } while (__any_sync(0xffffffffu, u.x != cnt || u.w != cnt || v.x != cnt || v.w != cnt));
            const uint32_t y = pack_bf16(__uint_as_float(u.y) + __uint_as_float(v.y), __uint_as_float(u.z) + __uint_as_float(v.z));
            xo = pack_bf16(bf_lo(xo) + bf_lo(y), bf_hi(xo) + bf_hi(y));
        }
        if (half) TS(TB + 7); else TS(TB + 3);
        if (!half && !ffn) continue;
        const uint32_t xw = movm(xo);
        if (TAIL && half) {
            reinterpret_cast<uint32_t*>(p.out)[wq * 32 + lane] = xw;
            if (wq == 0) {
                if (lane < 16) g_s.ticket[lane >> 3][lane & 7][0] = 0;
                if (lane == 16) g_s.epoch = (tag >> 2) + 1;
            }
            break;
        }
        if (!TAIL) {
            mbar_wait(SM_WBAR, qs && ffn);
            __syncwarp();
#pragma unroll
            for (int ks = 0; ks < NPRE; ks++) {
                ldsm4t(f[ks], a0 + ks * kstride);
                ldsm4t(f[ks] + 4, a1 + ks * kstride);
            }
        }
        if (half) TS(8); else TS(TB + 4);
        ln_gemv_part<NPRE>(f, a0, a1, kstride, xw, wq, lane);
        const uint32_t wd0 = Z_GU + USTR + wq * 2048 + ((lane & 7) + (lane >> 4) * 8) * 128 + ((((lane >> 3) & 1) ^ (lane & 7)) << 4);
        uint32_t d[4][4];
        constexpr int DPRE = TAIL ? 4 : MID_DPRE;
#pragma unroll
        for (int mt = 0; mt < DPRE; mt++) ldsm4t(d[mt], wd0 ^ (mt << 5));
        uint4* out = qs ? q_dst(p, 1, cta, lane) : &g_s.ar[TAIL ? 3 : 1][cta & 1][wq * 16 + (lane >> 1)][lane & 1];
        __syncthreads();
        if (!half) TS(TB + 5);
        if (WQ_EARLY && !TAIL && !half && wq == 4) load_wq(tm, cta, 0, z);
        float r = ln_gemv_fin(lane);
        if (qs) {
            if (wq == 0) publish_q(out, r, tag, lane);
            if (cta == 0)
                asm volatile("st.relaxed.gpu.global.b64 [%0], %1;" ::"l"(&g_s.x2[wq * 32 + lane]), "l"((unsigned long long)tag << 32 | xo) : "memory");
            __syncthreads();
            TS(9);
            break;
        }
        r = bf16r(r);
        const float up = __shfl_down_sync(0xffffffffu, r, 16);
#pragma unroll
        for (int mt = DPRE; mt < 4; mt++) ldsm4t(d[mt], wd0 ^ (mt << 5));
        const float hh = (r > 0.f ? r : 0.f * r) * up;
        const float h0 = __shfl_sync(0xffffffffu, hh, 2 * t), h1 = __shfl_sync(0xffffffffu, hh, 2 * t + 1);
        const float h2 = __shfl_sync(0xffffffffu, hh, 2 * t + 8), h3 = __shfl_sync(0xffffffffu, hh, 2 * t + 9);
        const uint32_t b0 = pack_bf16(h0, h1), b1 = pack_bf16(h2, h3);
        float c0[4] = {0.f, 0.f, 0.f, 0.f}, c1[4] = {0.f, 0.f, 0.f, 0.f};
#pragma unroll
        for (int mt = 0; mt < 4; mt++) {
            const bool mine = (g >> 1) == mt;
            mma((mt & 1) ? c1 : c0, d[mt], mine ? b0 : 0u, mine ? b1 : 0u);
        }
        ar_add(out, c0[0] + c1[0], c0[2] + c1[2]);
        TS(TB + 6);
        if (!TAIL) {
            if (wq == 4 || wq == 5) bar_sync(4, 256); else bar_arrive(4, 256);
        }
    }
}

#define UVARS                                                                                               \
    const int wqu = __shfl_sync(0xffffffffu, tid_now() >> 5, 0);                                            \
    const int wg = wqu >> 2, wj = wqu & 3;                                                                  \
    [[maybe_unused]] const int head = unit_head(cta, wg), ui = unit_index(cta, wg), tb = head * NTILE;      \
    [[maybe_unused]] const uint32_t slots = SM_SLOTS + wg * USTR, bars = SM_BAR + wg * 48;                  \
    [[maybe_unused]] const int barid = 1 + wg;                                                              \
    [[maybe_unused]] const uint32_t qbase = cta < 128 ? SM_Q : SM_WG + wg * 1024;                           \
    [[maybe_unused]] const uint32_t rec = SM_ST + wg * 16;                                                  \
    [[maybe_unused]] const uint32_t mx = SM_MX + wg * 64;
#define Q_RD (qbase + (lane & 15) * 16)
#define P_RD (SM_P + wg * 512 + (lane & 15) * 16)
#define P_WR (SM_P + wg * 512 + (wj >> 1) * 256 + (wj & 1) * 8 + (lane & 15) * 16)

__device__ __forceinline__ void static_phase(const Maps& tm, const int cta, Acc& acc, uint32_t (*rp)[48]) {
    UVARS
#pragma unroll 1
    for (int rv = 0; rv < NSTAT; rv++) {
        const int rn = __shfl_sync(0xffffffffu, rv, 0);
        const int lane = tid_now() & 31;
        const uint32_t d = (uint32_t)(0x10210432105432ull >> (8 * rn)), par = 0x7c0u >> (2 * rn);
        const int sk = d & 7, sv = (d >> 4) & 7;
        Pack pk;
        pk.cmp = SM_CMP + wg * 32;
        pk.esc = SM_ESC + wg * (ECAP * 8);
        pk.key = (rn < 4 ? rn + 3 : 6 - rn) << 11 | wj << 5 | lane;
        const bool inplace = rn < 4;
        const uint32_t dst = slots + 2 * SLOT + (6 - rn) * 24576 + (wj * 32 + lane) * 16;
        const uint32_t kb = k_offset(slots, wj, lane) + sk * SLOT;
        float s[4] = {0.f, 0.f, 0.f, 0.f}, s2[4] = {0.f, 0.f, 0.f, 0.f};
        uint32_t a[16];
        mbar_wait(bars + sk * 8, par & 1);
        __syncwarp();
        {
            const uint32_t b4 = lds32(pk.cmp);
#pragma unroll SUNR
            for (int h = 0; h < 2; h++) {
                const uint32_t k = kb + h * 8192, e = dst + h * 6144;
                load_khalf(a, k);
                qk_half(s, s2, a, Q_RD + h * 512);
                pack16(a, b4, inplace ? k : e, inplace ? k ^ 32 : e + 2048, inplace ? k ^ 64 : e + 4096, h, pk);
            }
        }
#pragma unroll
        for (int i = 0; i < 4; i++) s[i] += s2[i];
        softmax_step(s, acc, P_WR, mx, barid, lane, wj);
        const uint32_t vb = v_offset(slots, wj, lane) + sv * SLOT;
        mbar_wait(bars + sv * 8, (par >> 1) & 1);
        __syncwarp();
        {
            const uint32_t b4 = lds32(pk.cmp + 4);
#pragma unroll SUNR
            for (int y = 0; y < 2; y++) {
                const uint32_t v = vb + y * 4096, e = dst + 12288 + y * 6144;
                load_vhalf(a, v);
                pv_half(acc, a, P_RD + y * 256);
                pack16(a, b4, inplace ? v : e, inplace ? v ^ 32 : e + 2048, inplace ? v + 2048 : e + 4096, 2 + y, pk);
            }
        }
        if (rn == 0) park(rp[0], kb, vb);
        if (rn == 1) park(rp[1], kb, vb);
        if (rn == 2) park(rp[2], kb, vb);
        if (rn == 3) park(rp[3], kb, vb);
        asm volatile("fence.proxy.async.shared::cta;" ::: "memory");
        wg_bar_or(barid, false);
        const int j = (int)((wj == 1 ? 0xe0c0a86u : 0xfd0b907u) >> (4 * rn)) & 15;
        if ((wj == 1 || wj == 2) && j) issue_item(j, tm, tb, ui, slots, bars);
        if (wj == 0) {
            const uint32_t st = lds32(rec + 4);
            if (lane == 0 && lds32(pk.cmp + 8) > ECAP) {
                sts16(SM_KEEP + wg * 64 + (st & 255) * 2, rn * NUNIT + ui);
                sts32(rec + 4, (st + 1) | 0x10000u << (pk.key >> 11));
            }
            __syncwarp();
        }
    }
    TSD(28);
    if (wqu == 0) __threadfence();
    wg_bar_or(barid, false);
}

__device__ __forceinline__ void acc_init(Acc& a) {
#pragma unroll
    for (int i = 0; i < 4; i++) { a.o[0][i] = 0.f; a.o[1][i] = 0.f; a.l[i] = 0.f; }
    a.m0 = a.m1 = __int_as_float(0xff800000);
}

__device__ __forceinline__ void attention_pass(const Maps& tm, const Params& p, const int cta, const int ph, const uint32_t tag0,
                                               Acc& acc, uint32_t (*rp)[48], float* s) {
    UVARS
    const int lim = ph ? T_KEEP0 : NTILE;
    uint32_t ticket = 0;
    if (wj == 0) draw_ticket(ticket, p, ph, head, tid_now() & 31);
    const uint32_t st0 = __shfl_sync(0xffffffffu, lds32(rec + 4), 0);
    uint32_t phbits = __shfl_sync(0xffffffffu, lds32(rec + 12), 0);
    int nk = st0 & 255;
    uint32_t cur = DESC(0, 1) | 256;
    uint32_t q0 = 0, q1 = 0;
    int rn = NSTAT, ki = 0, since = KRATIO;
    bool open = true;
    if (ph) {
        rn = 0; q0 = cur; cur = 128 | 8;
        if (nk > 0 && __shfl_sync(0xffffffffu, (int)lds16(SM_KEEP + wg * 64 + nk * 2 - 2), 0) >= T_KEEP0) nk--;
        else cur |= 512;
    }
#pragma unroll 1
    while (true) {
        const int lane = tid_now() & 31;
        const uint32_t rel = cur ? cur : (rn == 1 ? DESC(2, 3) : 0);
        const int sk = rel & 7, sv = (rel >> 3) & 7;
        const bool keeps = ph && ki < nk && (rel & 64);
        const bool want = (rel & 64) && open && (!(q0 & 256) || (keeps && since < KRATIO));
        int tkeep = 0;
        if (keeps) tkeep = __shfl_sync(0xffffffffu, lds16(SM_KEEP + wg * 64 + ki * 2), 0);
        const bool resid = rn + (cur == 0) < NSTAT;
#define PUBLISH()                                                                                                          \
        if (wj == 0) {                                                                                                     \
            uint32_t lb = 0;                                                                                               \
            if (resid && q0 && mbar_test(bars + ((q0 >> 3) & 7) * 8, (phbits >> ((q0 >> 3) & 7)) & 1)) lb = 0x10000u;      \
            asm volatile("{\n.reg .pred p, q;\n.reg .u32 w;\nmov.u32 w, %6;\nsetp.eq.u32 p, %7, 0;\n@p bra.uni N_%=;\n"  \
                         "shfl.sync.idx.b32 w, %1, 0, 31, 0xffffffff;\nadd.u32 w, w, %5;\nmin.u32 w, w, %6;\nN_%=:\n"      \
                         "setp.eq.u32 p, %2, 0;\nsetp.ge.and.u32 q, w, %3, p;\nor.b32 w, w, %8;\n@q or.b32 w, w, 0x20000;\n" \
                         "@p st.shared.u32 [%0], w;\n@q red.relaxed.gpu.global.add.u32 [%4], 1;\n}"                        \
                         ::"r"(rec), "r"(ticket), "r"(lane), "r"((!resid && !q0 && !keeps) ? lim : NTILE + 1),             \
                           "l"(&g_s.done[lane]), "n"(T_DYN0 + NUNIT), "n"(NTILE), "r"((uint32_t)want), "r"(lb) : "memory"); \
        }
        if (cur ? !(cur & 512) : !(st0 >> (16 + rn) & 1)) {
            Pack pk;
            pk.cmp = SM_CMP + wg * 32;
            pk.esc = SM_ESC + wg * (ECAP * 8);
            pk.key = rn << 11 | wj << 5 | lane;
            uint32_t a[16], vb, flags = 0;
            if (cur) {
                vb = v_offset(slots, wj, lane) + sv * SLOT;
                if (cur & 64) {
                    const uint32_t kb = k_offset(slots, wj, lane) + sk * SLOT;
                    float s2[4] = {0.f, 0.f, 0.f, 0.f};
                    s[0] = s[1] = s[2] = s[3] = 0.f;
                    mbar_wait(bars + sk * 8, (phbits >> sk) & 1);
                    __syncwarp();
                    if (DBG_U && ph == DBG_PH) TSW(26);
                    load_khalf(a, kb);
                    qk_half(s, s2, a, Q_RD);
                    load_khalf(a, kb + 8192);
                    qk_half(s, s2, a, Q_RD + 512);
                    mbar_wait(bars + sv * 8, (phbits >> sv) & 1);
                    __syncwarp();
                    phbits ^= 1u << sk | 1u << sv;
#pragma unroll
                    for (int i = 0; i < 4; i++) s[i] += s2[i];
                }
                load_vhalf(a, vb);
            } else {
                vb = slots + 2 * SLOT + min(rn, 2) * 24576 + (wj * 32 + lane) * 16;
                flags = lds32(pk.cmp + 16 + wj * 4) >> (rn * 4);
                if (rn == 3) unpark(rp[0], vb);
                if (rn == 4) unpark(rp[1], vb);
                if (rn == 5) unpark(rp[2], vb);
                if (rn == 6) unpark(rp[3], vb);
                const uint2 b4 = lds64(pk.cmp);
                float s2[4] = {0.f, 0.f, 0.f, 0.f};
                s[0] = s[1] = s[2] = s[3] = 0.f;
#pragma unroll RUNR
                for (int h = 0; h < 2; h++) {
                    unpack16(a, b4.x, vb + h * 6144, h, flags, pk);
                    qk_half(s, s2, a, Q_RD + h * 512);
                }
                unpack16(a, b4.y, vb + 12288, 2, flags, pk);
#pragma unroll
                for (int i = 0; i < 4; i++) s[i] += s2[i];
            }
            softmax_step(s, acc, P_WR, mx, barid, lane, wj);
            pv_half(acc, a, P_RD);
            if (cur) load_vhalf(a, vb + 4096);
            else unpack16(a, lds32(pk.cmp + 4), vb + 18432, 3, flags, pk);
            pv_half(acc, a, P_RD + 256);
        } else {
            wg_bar_or(barid, false);
        }
        PUBLISH();
        bar_sync(8 + wg, 128);
        const uint32_t w = __shfl_sync(0xffffffffu, lds32(rec), 0);
        if (w & 0x20000u) break;
        if (cur == 0) rn++;
        int tv = w & 0xffff;
        uint32_t push = 0;
        const bool streamed = tv < lim;
        if (streamed) push = (rel & 127) | 256;
        else if (keeps) { tv = tkeep; push = rel & 127; }
        else if (cur & 128) tv = T_DYN0 + ui;
        if (wj == 1 ? push != 0 : wj == 2 && (push | (cur & 128))) {
            const int sl = wj == 1 ? sk : sv;
            tma_tile(wj == 1 ? &tm.k : &tm.v, tb + tv, slots + sl * SLOT, bars + sl * 8);
            if (!ph && tv >= T_KEEP0 && tv < T_KEEPEND) l2_prefetch((wj == 1 ? p.k : p.v) + (size_t)(tb + tv) * SLOT, SLOT, POL_NORMAL);
        }
        if (streamed) {
            since++;

            if (!ph && tv >= T_KEEP0) {
                if (wj == 3 && lane == 0) sts16(SM_KEEP + wg * 64 + nk * 2, tv);
                nk++;
                if (nk >= KEEPCAP) open = false;
            }
            if (open && wj == 0) draw_ticket(ticket, p, ph, head, lane);
        } else {
            if (want) open = false;
            if (keeps) { ki++; since = 0; }
        }
        if (q0) q1 |= push; else q0 = push;
        if (resid && (q0 == 0 || (!(w & 0x10000u) && (rn < 2 || streamed)))) {
            cur = 0;
        } else {
            cur = q0; q0 = q1; q1 = 0;
        }
    }
    const int lane = tid_now() & 31;
    {
        const int e = (lane >> 1) & 1;
        float l = e ? acc.l[1] : acc.l[0], m = e ? acc.m1 : acc.m0;
        float inv; asm("rcp.approx.ftz.f32 %0, %1;" : "=f"(inv) : "f"(l));
        float lg; asm("lg2.approx.ftz.f32 %0, %1;" : "=f"(lg) : "f"(l));
        uint32_t lam = __float_as_uint(m + lg);
        const uint32_t t16 = (tag0 + ph + 1) & 0xffffu;
        uint32_t ta = (lam & 0xffff0000u) | t16, tc = (lam << 16) | t16;
        uint4* dst = part_dst(p, head, ui, wqu * 32 + lane);
        ll_st(dst, __float_as_uint((e ? acc.o[0][1] : acc.o[0][0]) * inv), ta,
                   __float_as_uint((e ? acc.o[0][3] : acc.o[0][2]) * inv), tc);
        ll_st(dst + 4 * NUNIT * 2, __float_as_uint((e ? acc.o[1][1] : acc.o[1][0]) * inv), ta,
                                   __float_as_uint((e ? acc.o[1][3] : acc.o[1][2]) * inv), tc);
    }
    if (ph) TSW(38); else TSW(36);
    if (wj == 0 && lane == 0) {
        sts32(rec + 4, nk | (st0 & 0xffff0000u));
        sts32(rec + 12, phbits);
    }
}

__global__ void __launch_bounds__(256, 1)
fused_kernel(const __grid_constant__ Maps tm, const Params p) {
    extern __shared__ __align__(1024) unsigned char smem_raw[];
    const int cta = blockIdx.x;
    const bool worker = cta < 128;
    uint32_t tag0;
    if ((uint32_t)__cvta_generic_to_shared(smem_raw) != SM_BASE) __trap();
    TS(40);
    uint32_t rp[4][48];
    Acc acc;
    {
        UVARS
        const int lane = tid_now() & 31;
        if (wj == 0) {
#pragma unroll
            for (int i = 0; i < 6; i++) mbar_init(bars + i * 8, 1);
            mbar_init(SM_WBAR + wg * 8, 2);
            mbar_init(SM_DBAR + wg * 8, 1);
            asm volatile("fence.proxy.async.shared::cta;" ::: "memory");
            __syncwarp();
            if (worker && wg == 0) {
                load_wq(tm, cta, 0, SM_SLOTS + SLOT);
                load_wq(tm, cta, 1, SM_SLOTS + USTR + SLOT);
            }
            issue_item(0, tm, tb, ui, slots, bars);
            issue_item(1, tm, tb, ui, slots, bars);
            if (worker && wg == 0 && lane < 16) ll_st(q_dst(p, 0, cta, lane), 0, 0, 0, 0);
        }
        if (wj == 1) {
            if (lane < ECAP) sts64(SM_ESC + wg * (ECAP * 8) + lane * 8, 0xffffffffu, 0);
            if (lane < 8) sts32(SM_CMP + wg * 32 + lane * 4, 0);
            if (lane < 4) sts32(rec + lane * 4, lane == 3 ? 0x27 : 0);
        }
        if (wj == 2) {
            const uint4 u = *reinterpret_cast<const uint4*>(p.x + wg * 256 + lane * 8);
            sts128(SM_P + wg * 512 + lane * 16, u.x, u.y, u.z, u.w);
        }
        if (wqu == 7 && worker && lane < 16) ll_st(&g_s.ar[0][0][0][0] + (cta * 8 + (lane >> 1)) * 8 + (lane & 1), 0, 0, 0, 0);
        if (wqu == 3) {
            uint32_t e;
            asm volatile("ld.relaxed.gpu.global.u32 %0, [%1];" : "=r"(e) : "l"(&g_s.epoch) : "memory");
            sts32(SM_RED, e * 4 + 1);
        }
        __syncthreads();
        tag0 = __shfl_sync(0xffffffffu, lds32(SM_RED), 0);
        const uint32_t xw = lds32(SM_P + wqu * 128 + lane * 4);
        __syncthreads();
        uint32_t it = 0;
        int item = 2;
#pragma unroll 1
        for (int stage = worker ? 0 : 1; stage < 3 || item < 6;) {
            if (item < (stage ? 6 : 5) && (wj != 1 || stage == 3 || mbar_test(bars + item * 8, 0))) {
                if (wj == 1) issue_item(item, tm, tb, ui, slots, bars);
                item++;
                continue;
            }
            spin_guard(it);
            if (stage == 0) {
                if (!mbar_test(SM_WBAR, 0)) continue;
                TS(32);
                const int row = wj * 64 + (lane & 7) + (lane >> 4) * 8;
                const uint32_t a0 = slots + SLOT + row * 64 + ((((lane >> 3) & 1) ^ ((lane >> 1) & 3)) << 4);
                uint32_t f[1][8];
                ldsm4t(f[0], a0);
                ldsm4t(f[0] + 4, a0 ^ 32);
                ln_gemv_part<1>(f, a0, a0 ^ 32, 1024, xw, wqu, lane);
                __syncthreads();
                if (wqu == 0) publish_q(q_dst(p, 0, cta, lane), ln_gemv_fin(lane), tag0, lane);
                if (wqu == 6 && cta < 112) {
                    expect_tx(SM_DBAR, SLOT);
                    tma_2d(&tm.wg, cta * 16, 0, SM_WG, SM_DBAR);
                    tma_2d(&tm.wg, cta * 16, 256, SM_WG + 8192, SM_DBAR);
                }
                __syncthreads();
                TS(33);
            } else if (stage == 1) {
                if (!mbar_test(bars + 2 * 8, 0) || !mbar_test(bars + 3 * 8, 0)) continue;
#pragma unroll 1
                for (int h = 0; h < 4; h++) {
                    uint32_t r[16], m = 0;
                    load_khalf(r, k_offset(slots, wj, lane) + 2 * SLOT + h * 8192);
#pragma unroll
                    for (int j = 0; j < 16; j++) m = __vmaxu2(m, r[j] & 0x7fff7fffu);
                    m = __reduce_max_sync(0xffffffffu, max(m >> 24, (m >> 8) & 0x7fu));
                    if (lane == 0)
                        asm volatile("red.shared.max.u32 [%0], %1;" ::"r"(SM_CMP + wg * 32 + (h & 2) * 2),
                                     "r"(min(max(m, 7u) - 7u, 113u) * 0x01010101u) : "memory");
                    __syncwarp();
                }
            } else {
                const uint4 v = ll_ld(&g_s.q[0][cta >> 7][head][wj * 32 + lane]);
                if (__any_sync(0xffffffffu, v.y != tag0 || v.w != tag0)) { delay_cycles(200); continue; }
                sts64(qbase + (wj * 32 + lane) * 8, v.x, v.z);
            }
            stage++;
        }
        wg_bar_or(barid, false);
        TS(34);
#pragma unroll
        for (int i = 0; i < 4; i++)
#pragma unroll
            for (int j = 0; j < 48; j++) asm volatile("" : "=r"(rp[i][j]));
        acc_init(acc);
    }
    static_phase(tm, cta, acc, rp);
    float s[4] = {0.f, 0.f, 0.f, 0.f};
#pragma unroll 1
    for (int phv = 0;; phv = 1) {
        const int ph = __shfl_sync(0xffffffffu, phv, 0);
        attention_pass(tm, p, cta, ph, tag0, acc, rp, s);
        if (ph) break;
        uint32_t rx[32];
        {
            UVARS
            load_kfrag(rx, k_offset(slots, wj, tid_now() & 31));
            wg_bar_or(barid, false);
            if (worker && wj == 3) tma_rows(&tm.wo, cta * 32 + wg * 16, slots, SM_WBAR);
            if (cta < 112) mbar_wait(SM_DBAR, 0);
            __syncwarp();
        }
        if (worker) gemv_chain<false>(tm, p, cta, tag0 + 1);
        UVARS
        const int lane = tid_now() & 31;
        const uint4* src = &g_s.q[1][cta >> 7][head][wj * 32 + lane];
        uint4 v;
        uint32_t it = 0;
        do {
            spin_guard(it);
            if (it == 1 || !worker) delay_cycles(D_AG);
            v = ll_ld(src);
            if (it == 1 && wj == 1) tma_tile(&tm.k, tb + T_DYN0 + ui, slots, bars);
        } while (__any_sync(0xffffffffu, v.y != tag0 + 1 || v.w != tag0 + 1));
        sts64(qbase + (wj * 32 + lane) * 8, v.x, v.z);
        wg_bar_or(barid, false);
        TS(10);
        float s2[4] = {0.f, 0.f, 0.f, 0.f};
        s[0] = s[1] = s[2] = s[3] = 0.f;
        qk_half(s, s2, rx, Q_RD);
        qk_half(s, s2, rx + 16, Q_RD + 512);
#pragma unroll
        for (int i = 0; i < 4; i++) s[i] += s2[i];
        acc_init(acc);
    }
    if (worker) {
        UVARS
        if (wj == 3) tma_rows(&tm.wo, cta * 32 + wg * 16, slots + 2 * SLOT, SM_TBAR);
        if (wj == 2 && cta < 112) load_ffn(tm, cta, wg, slots + 3 * SLOT);
        gemv_chain<true>(tm, p, cta, tag0 + 2);
    }
}

typedef CUresult (*EncodeFn)(CUtensorMap*, CUtensorMapDataType, cuuint32_t, void*, const cuuint64_t*, const cuuint64_t*,
                             const cuuint32_t*, const cuuint32_t*, CUtensorMapInterleave, CUtensorMapSwizzle,
                             CUtensorMapL2promotion, CUtensorMapFloatOOBfill);

void make_map(EncodeFn encode, CUtensorMap* m, void* base, int rank, const cuuint64_t* gd, const cuuint64_t* gs,
              const cuuint32_t* bx, CUtensorMapSwizzle sw) {
    const cuuint32_t es[3] = {1, 1, 1};
    encode(m, CU_TENSOR_MAP_DATA_TYPE_BFLOAT16, rank, base, gd, gs, bx, es, CU_TENSOR_MAP_INTERLEAVE_NONE, sw,
           CU_TENSOR_MAP_L2_PROMOTION_NONE, CU_TENSOR_MAP_FLOAT_OOB_FILL_NONE);
}

}

extern "C" void kernel_launch(void* const* d_in, const int* in_sizes, int n_in, void* d_out, int out_size) {
    (void)in_sizes; (void)n_in; (void)out_size;
    static EncodeFn encode = nullptr;
    static void* scratch = nullptr;
    if (!encode) {
        void* fn = nullptr;
        cudaDriverEntryPointQueryResult qr;
        cudaGetDriverEntryPoint("cuTensorMapEncodeTiled", &fn, cudaEnableDefault, &qr);
        encode = (EncodeFn)fn;
        cudaGetSymbolAddress(&scratch, g_scratch);
        cudaFuncSetAttribute(fused_kernel, cudaFuncAttributeMaxDynamicSharedMemorySize, SM_TOTAL);
    }
    Maps tm;
    {
        const cuuint64_t gd[3] = {64, 8ull * 65536ull, 2}, gs[2] = {256, 128};
        const cuuint32_t bx[3] = {64, 64, 2};
        make_map(encode, &tm.k, d_in[1], 3, gd, gs, bx, CU_TENSOR_MAP_SWIZZLE_128B);
        make_map(encode, &tm.v, d_in[2], 3, gd, gs, bx, CU_TENSOR_MAP_SWIZZLE_128B);
    }
    {
        const cuuint64_t gd[2] = {4096, 512}, gs[1] = {8192};
        const cuuint32_t bx[2] = {32, 256};
        make_map(encode, &tm.wq, d_in[3], 2, gd, gs, bx, CU_TENSOR_MAP_SWIZZLE_64B);
    }
    {
        const cuuint64_t gd[3] = {64, 4096, 8}, gs[2] = {1024, 128};
        const cuuint32_t bx[3] = {64, 16, 8};
        make_map(encode, &tm.wo, d_in[4], 3, gd, gs, bx, CU_TENSOR_MAP_SWIZZLE_128B);
        const cuuint64_t gd2[3] = {64, 1792, 8};
        make_map(encode, &tm.wd, d_in[8], 3, gd2, gs, bx, CU_TENSOR_MAP_SWIZZLE_128B);
    }
    {
        const cuuint64_t gd[2] = {1792, 512}, gs[1] = {3584};
        const cuuint32_t bx[2] = {16, 256};
        make_map(encode, &tm.wg, d_in[6], 2, gd, gs, bx, CU_TENSOR_MAP_SWIZZLE_32B);
        make_map(encode, &tm.wu, d_in[7], 2, gd, gs, bx, CU_TENSOR_MAP_SWIZZLE_32B);
    }
    Params p;
    p.x = (const __nv_bfloat16*)d_in[0];
    p.k = (const char*)d_in[1];
    p.v = (const char*)d_in[2];
    p.wq = (const char*)d_in[3];
    p.wo = (const char*)d_in[4];
    p.wg = (const char*)d_in[6];
    p.wu = (const char*)d_in[7];
    p.wd = (const char*)d_in[8];
    p.out = (__nv_bfloat16*)d_out;
    p.s = (Scratch*)scratch;
    fused_kernel<<<NCTA, 256, SM_TOTAL, cudaStreamPerThread>>>(tm, p);
}
```

```cpp
#include <cuda_runtime.h>
#include <cuda_bf16.h>
#include <cuda.h>
#include <stdint.h>

namespace {

constexpr int NCTA      = 132;
constexpr int NUNIT     = 33;
constexpr int NTILE     = 1024;
constexpr int SLOT      = 16384;
constexpr int NSTAT     = 7;
constexpr int T_DYN0    = NSTAT * NUNIT;
#define NKEEP 198
#define KEEP_TAILSKIP 33
#define KRATIO 1
#define D_AR 650
#define D_SKIP 1500
#define WQ_EARLY 1
#define D_AG 200
#define PF_REM 0
#define RUNROLL 1
#define SUNROLL 1
#define MID_NPRE 2
#define S1_NPRE 2
#define MID_DPRE 0
#define ECAP 24
#define DBG_U 0
#define DBG_PH 0
constexpr int T_KEEP0   = NTILE - NKEEP;
constexpr int T_KEEPEND = NTILE - KEEP_TAILSKIP;
constexpr int SUNR      = SUNROLL, RUNR = RUNROLL;
constexpr int KEEPCAP   = 32;
constexpr unsigned SPIN_LIMIT = 1u << 22;

constexpr uint32_t SM_BASE  = 1024;
constexpr uint32_t USTR     = 2 * SLOT + 3 * 24576;
constexpr uint32_t SM_SLOTS = SM_BASE;
constexpr uint32_t SM_WG    = SM_SLOTS + 2 * USTR;
constexpr uint32_t SM_Q     = SM_WG + SLOT;
constexpr uint32_t SM_P     = SM_Q + 1024;
constexpr uint32_t SM_RED   = SM_P + 1024;
constexpr uint32_t SM_MX    = SM_RED;
constexpr uint32_t SM_BAR   = SM_RED + 192;
constexpr uint32_t SM_WBAR  = SM_BAR + 96;
constexpr uint32_t SM_TBAR  = SM_BAR + 104;
constexpr uint32_t SM_DBAR  = SM_BAR + 112;
constexpr uint32_t SM_KEEP  = SM_BAR + 128;
constexpr uint32_t SM_ST    = SM_KEEP + 128;
constexpr uint32_t SM_CMP   = SM_ST + 32;
constexpr uint32_t SM_ESC   = SM_CMP + 64;
constexpr int SM_TOTAL      = SM_ESC + 2 * ECAP * 8 - SM_BASE;
static_assert(SM_TOTAL <= 232448 && ECAP <= 32, "smem");

struct Scratch {
    uint4 part[128][8][NUNIT][2];
    uint4 ar[4][2][128][8];
    uint2 x2[256];
    uint4 q[2][2][8][128];
    unsigned ticket[2][8][32];
    unsigned done[32];
    unsigned epoch;
};
__device__ Scratch g_scratch;
#define g_s (*p.s)
#define TS(i)
#define TSD(i)
#define TSW(i)
#define TT(ph, head, tile)

struct Maps { CUtensorMap k, v, wq, wo, wg, wu, wd; };
struct Params {
    const __nv_bfloat16* x;
    const char* k;
    const char* v;
    const char* wq;
    const char* wo;
    const char* wg;
    const char* wu;
    const char* wd;
    __nv_bfloat16* out;
    Scratch* s;
};

__device__ __forceinline__ void mbar_init(uint32_t bar, uint32_t cnt) {
    asm volatile("{\n.reg .pred p;\nelect.sync _|p, 0xffffffff;\n@p mbarrier.init.shared::cta.b64 [%0], %1;\n}" ::"r"(bar), "r"(cnt) : "memory");
}
__device__ __forceinline__ void mbar_wait(uint32_t bar, uint32_t parity) {
    asm volatile("{\n.reg .pred p, q;\n.reg .u32 c;\n"
                 "mbarrier.try_wait.parity.shared::cta.b64 p, [%0], %1;\n@p bra D_%=;\nmov.u32 c, 0;\n"
                 "W_%=:\nmbarrier.try_wait.parity.shared::cta.b64 p, [%0], %1;\nadd.u32 c, c, 1;\n"
                 "setp.lt.and.u32 q, c, %2, !p;\n@q bra W_%=;\n@!p trap;\nD_%=:\n}"
                 ::"r"(bar), "r"(parity), "n"(SPIN_LIMIT) : "memory");
}
__device__ __forceinline__ void spin_guard(uint32_t& it) {
    asm volatile("{\n.reg .pred q;\nadd.u32 %0, %0, 1;\nsetp.gt.u32 q, %0, %1;\n@q trap;\n}" : "+r"(it) : "n"(SPIN_LIMIT));
}
constexpr uint64_t POL_FIRST = 0x12f0000000000000ull, POL_NORMAL = 0x16f0000000000000ull;
__device__ __forceinline__ void tma_rows(const CUtensorMap* tm, int row, uint32_t dst, uint32_t bar) {
    asm volatile("{\n.reg .pred p;\nelect.sync _|p, 0xffffffff;\n"
                 "@p mbarrier.arrive.expect_tx.shared::cta.b64 _, [%4], %6;\n"
                 "@p cp.async.bulk.tensor.3d.shared::cluster.global.mbarrier::complete_tx::bytes.L2::cache_hint "
                 "[%0], [%1, {%2, %3, %2}], [%4], %5;\n}"
                 ::"r"(dst), "l"(tm), "r"(0), "r"(row), "r"(bar), "l"(POL_FIRST), "r"(SLOT) : "memory");
}
__device__ __forceinline__ void tma_tile(const CUtensorMap* tm, int gtile, uint32_t dst, uint32_t bar) {
    tma_rows(tm, gtile * 64, dst, bar);
}
__device__ __forceinline__ void expect_tx(uint32_t bar, uint32_t bytes) {
    asm volatile("{\n.reg .pred p;\nelect.sync _|p, 0xffffffff;\n@p mbarrier.arrive.expect_tx.shared::cta.b64 _, [%0], %1;\n}"
                 ::"r"(bar), "r"(bytes) : "memory");
}
__device__ __forceinline__ void tma_2d(const CUtensorMap* tm, int c0, int c1, uint32_t dst, uint32_t bar) {
    asm volatile("{\n.reg .pred p;\nelect.sync _|p, 0xffffffff;\n"
                 "@p cp.async.bulk.tensor.2d.shared::cluster.global.mbarrier::complete_tx::bytes.L2::cache_hint "
                 "[%0], [%1, {%2, %3}], [%4], %5;\n}"
                 ::"r"(dst), "l"(tm), "r"(c0), "r"(c1), "r"(bar), "l"(POL_FIRST) : "memory");
}
__device__ __forceinline__ void l2_prefetch(const void* p, uint32_t bytes, uint64_t pol) {
    asm volatile("{\n.reg .pred p;\nelect.sync _|p, 0xffffffff;\n"
                 "@p cp.async.bulk.prefetch.L2.global.L2::cache_hint [%0], %1, %2;\n}" ::"l"(p), "r"(bytes), "l"(pol) : "memory");
}
__device__ __forceinline__ void ldsm4(uint32_t* r, uint32_t a) {
    asm volatile("ldmatrix.sync.aligned.m8n8.x4.shared.b16 {%0,%1,%2,%3}, [%4];"
                 : "=r"(r[0]), "=r"(r[1]), "=r"(r[2]), "=r"(r[3]) : "r"(a) : "memory");
}
__device__ __forceinline__ void ldsm4t(uint32_t* r, uint32_t a) {
    asm volatile("ldmatrix.sync.aligned.m8n8.x4.trans.shared.b16 {%0,%1,%2,%3}, [%4];"
                 : "=r"(r[0]), "=r"(r[1]), "=r"(r[2]), "=r"(r[3]) : "r"(a) : "memory");
}
__device__ __forceinline__ void mma(float* c, const uint32_t* a, uint32_t b0, uint32_t b1) {
    asm volatile("mma.sync.aligned.m16n8k16.row.col.f32.bf16.bf16.f32 {%0,%1,%2,%3}, {%4,%5,%6,%7}, {%8,%9}, {%0,%1,%2,%3};"
                 : "+f"(c[0]), "+f"(c[1]), "+f"(c[2]), "+f"(c[3])
                 : "r"(a[0]), "r"(a[1]), "r"(a[2]), "r"(a[3]), "r"(b0), "r"(b1));
}
__device__ __forceinline__ uint32_t movm(uint32_t a) {
    uint32_t d; asm volatile("movmatrix.sync.aligned.m8n8.trans.b16 %0, %1;" : "=r"(d) : "r"(a)); return d;
}
__device__ __forceinline__ uint32_t pack_bf16(float lo, float hi) {
    uint32_t d; asm("cvt.rn.bf16x2.f32 %0, %1, %2;" : "=r"(d) : "f"(hi), "f"(lo)); return d;
}
__device__ __forceinline__ float bf16r(float v) { return __uint_as_float(pack_bf16(v, 0.f) << 16); }
__device__ __forceinline__ float bf_lo(uint32_t w) { return __uint_as_float(w << 16); }
__device__ __forceinline__ float bf_hi(uint32_t w) { return __uint_as_float(w & 0xffff0000u); }
__device__ __forceinline__ float ex2(float v) { float d; asm("ex2.approx.ftz.f32 %0, %1;" : "=f"(d) : "f"(v)); return d; }
__device__ __forceinline__ uint4 lds128(uint32_t a) {
    uint4 v; asm volatile("ld.shared.v4.u32 {%0,%1,%2,%3}, [%4];" : "=r"(v.x), "=r"(v.y), "=r"(v.z), "=r"(v.w) : "r"(a) : "memory"); return v;
}
__device__ __forceinline__ uint2 lds64(uint32_t a) {
    uint2 v; asm volatile("ld.shared.v2.u32 {%0,%1}, [%2];" : "=r"(v.x), "=r"(v.y) : "r"(a) : "memory"); return v;
}
__device__ __forceinline__ uint32_t lds32(uint32_t a) {
    uint32_t v; asm volatile("ld.shared.u32 %0, [%1];" : "=r"(v) : "r"(a) : "memory"); return v;
}
__device__ __forceinline__ void sts128(uint32_t a, uint32_t x, uint32_t y, uint32_t z, uint32_t w) {
    asm volatile("st.shared.v4.u32 [%0], {%1,%2,%3,%4};" ::"r"(a), "r"(x), "r"(y), "r"(z), "r"(w) : "memory");
}
__device__ __forceinline__ void sts64(uint32_t a, uint32_t x, uint32_t y) {
    asm volatile("st.shared.v2.u32 [%0], {%1,%2};" ::"r"(a), "r"(x), "r"(y) : "memory");
}
__device__ __forceinline__ void sts32(uint32_t a, uint32_t x) {
    asm volatile("st.shared.u32 [%0], %1;" ::"r"(a), "r"(x) : "memory");
}
__device__ __forceinline__ void sts16(uint32_t a, uint32_t x) {
    asm volatile("st.shared.u16 [%0], %1;" ::"r"(a), "h"((unsigned short)x) : "memory");
}
__device__ __forceinline__ uint32_t lds16(uint32_t a) {
    unsigned short v; asm volatile("ld.shared.u16 %0, [%1];" : "=h"(v) : "r"(a) : "memory"); return v;
}
__device__ __forceinline__ bool wg_bar_or(int id, bool p) {
    uint32_t r;
    asm volatile("{\n.reg .pred a, b;\nsetp.ne.u32 a, %2, 0;\nbar.red.or.pred b, %1, 128, a;\nselp.u32 %0, 1, 0, b;\n}"
                 : "=r"(r) : "r"(id), "r"((uint32_t)p) : "memory");
    return r != 0;
}
__device__ __forceinline__ uint4 ll_ld(const uint4* p) {
    unsigned long long a, b;
    asm volatile("ld.relaxed.gpu.global.v2.b64 {%0,%1}, [%2];" : "=l"(a), "=l"(b) : "l"(p) : "memory");
    return make_uint4((uint32_t)a, (uint32_t)(a >> 32), (uint32_t)b, (uint32_t)(b >> 32));
}
__device__ __forceinline__ void ll_st(uint4* p, uint32_t v0, uint32_t t0, uint32_t v1, uint32_t t1) {
    unsigned long long a = ((unsigned long long)t0 << 32) | v0, b = ((unsigned long long)t1 << 32) | v1;
    asm volatile("st.relaxed.gpu.global.v2.b64 [%0], {%1,%2};" ::"l"(p), "l"(a), "l"(b) : "memory");
}
__device__ __forceinline__ uint4 ll_ld_last(const uint4* p) {
    unsigned long long a, b;
    asm volatile("ld.relaxed.gpu.global.L2::cache_hint.v2.b64 {%0,%1}, [%2], %3;" : "=l"(a), "=l"(b) : "l"(p), "l"(POL_FIRST) : "memory");
    return make_uint4((uint32_t)a, (uint32_t)(a >> 32), (uint32_t)b, (uint32_t)(b >> 32));
}
__device__ __forceinline__ void bar_sync(int id, int n) { asm volatile("bar.sync %0, %1;" ::"r"(id), "r"(n) : "memory"); }
__device__ __forceinline__ void bar_arrive(int id, int n) { asm volatile("bar.arrive %0, %1;" ::"r"(id), "r"(n) : "memory"); }
__device__ __forceinline__ void delay_cycles(int n) {
    if (n > 0) {
        uint32_t t0, t1;
        asm volatile("mov.u32 %0, %%clock;" : "=r"(t0));
        do { asm volatile("mov.u32 %0, %%clock;" : "=r"(t1)); } while (t1 - t0 < (uint32_t)n);
    }
}
__device__ __forceinline__ int tid_now() {
    int t; asm volatile("mov.u32 %0, %%tid.x;" : "=r"(t)); return t;
}
__device__ __forceinline__ bool mbar_test(uint32_t bar, uint32_t parity) {
    uint32_t ok;
    asm volatile("{\n.reg .pred p;\nmbarrier.test_wait.parity.shared::cta.b64 p, [%1], %2;\nselp.u32 %0, 1, 0, p;\n}"
                 : "=r"(ok) : "r"(bar), "r"(parity) : "memory");
    return ok != 0;
}

struct Acc {
    float o[2][4];
    float l[4];
    float m0, m1;
};

constexpr float SCALE_LOG2 = 0.08838834764831845f * 1.4426950408889634f;

__device__ __forceinline__ void softmax_step(float* s, Acc& a, uint32_t p_wr, uint32_t mx, int barid, int lane, int wj) {
#pragma unroll
    for (int i = 0; i < 4; i++) s[i] *= SCALE_LOG2;
    bool over = fmaxf(s[0], s[2]) > a.m0 || fmaxf(s[1], s[3]) > a.m1;
    {
        uint32_t b0 = movm(pack_bf16(ex2(s[0] - a.m0), ex2(s[1] - a.m1)));
        uint32_t b1 = movm(pack_bf16(ex2(s[2] - a.m0), ex2(s[3] - a.m1)));
        if (lane < 16) sts64(p_wr, b0, b1);
    }
    if (wg_bar_or(barid, over)) {
        float x0 = fmaxf(s[0], s[2]), x1 = fmaxf(s[1], s[3]);
#pragma unroll
        for (int d = 4; d < 32; d <<= 1) {
            x0 = fmaxf(x0, __shfl_xor_sync(0xffffffffu, x0, d));
            x1 = fmaxf(x1, __shfl_xor_sync(0xffffffffu, x1, d));
        }
        if (lane < 2) sts64(mx + wj * 16 + lane * 8, __float_as_uint(x0), __float_as_uint(x1));
        wg_bar_or(barid, false);
        float n0 = a.m0, n1 = a.m1;
#pragma unroll
        for (int j = 0; j < 4; j++) {
            uint2 v = lds64(mx + j * 16 + (lane & 1) * 8);
            n0 = fmaxf(n0, __uint_as_float(v.x));
            n1 = fmaxf(n1, __uint_as_float(v.y));
        }
        float f0 = ex2(a.m0 - n0), f1 = ex2(a.m1 - n1);
        a.m0 = n0; a.m1 = n1;
        a.o[0][0] *= f0; a.o[0][2] *= f0; a.o[1][0] *= f0; a.o[1][2] *= f0; a.l[0] *= f0; a.l[2] *= f0;
        a.o[0][1] *= f1; a.o[0][3] *= f1; a.o[1][1] *= f1; a.o[1][3] *= f1; a.l[1] *= f1; a.l[3] *= f1;
        uint32_t b0 = movm(pack_bf16(ex2(s[0] - n0), ex2(s[1] - n1)));
        uint32_t b1 = movm(pack_bf16(ex2(s[2] - n0), ex2(s[3] - n1)));
        if (lane < 16) sts64(p_wr, b0, b1);
        wg_bar_or(barid, false);
    }
}

__device__ __forceinline__ uint32_t mul2(uint32_t a, uint32_t b) {
    uint32_t d; asm("mul.rn.bf16x2 %0, %1, %2;" : "=r"(d) : "r"(a), "r"(b)); return d;
}
struct Pack {
    uint32_t cmp;
    uint32_t esc;
    uint32_t key;
};
__device__ __forceinline__ void pack16(const uint32_t* a, uint32_t up, uint32_t d0, uint32_t d1, uint32_t d2, int it,
                                       const Pack& pk) {
    const uint32_t dn = 0x7f007f00u - up;
    uint32_t l[8], n[4], bad = 0;
#pragma unroll
    for (int g = 0; g < 4; g++) {
        uint32_t z[4], e = 0;
#pragma unroll
        for (int j = 0; j < 4; j++) {
            z[j] = mul2(a[4 * g + j], dn);
            e |= mul2(z[j], up) ^ a[4 * g + j];
        }
        const uint32_t x0 = __byte_perm(z[0], z[1], 0x7531), x1 = __byte_perm(z[2], z[3], 0x7531);
        l[2 * g] = __byte_perm(z[0], z[1], 0x6420);
        l[2 * g + 1] = __byte_perm(z[2], z[3], 0x6420);
        n[g] = x0 | __funnelshift_l(x1, x1, 4);
        if (e | ((x0 | x1) & 0x78787878u)) bad |= 1u << g;
        if (g & 1) sts128(g == 1 ? d0 : d1, l[2 * g - 2], l[2 * g - 1], l[2 * g], l[2 * g + 1]);
    }
    sts128(d2, n[0], n[1], n[2], n[3]);
    if (bad) {
        asm volatile("red.shared.or.b32 [%0], %1;" ::"r"(pk.cmp + 16 + ((pk.key >> 3) & 12)),
                     "r"(1u << ((pk.key >> 11) * 4 + it)) : "memory");
#pragma unroll
        for (int g = 0; g < 4; g++) {
            asm volatile("{\n.reg .pred p;\n.reg .u32 i;\nsetp.ne.u32 p, %0, 0;\nmov.u32 i, %5;\n"
                         "@p st.shared.v2.u32 [%6], {%7, %8};\n@p st.shared.u32 [%9], %10;\n"
                         "@p atom.shared.inc.u32 i, [%1], 0xfffffffe;\nsetp.lt.u32 p, i, %5;\nmad.lo.u32 i, i, 8, %2;\n"
                         "@p st.shared.v2.u32 [i], {%3, %4};\n}"
                         ::"r"(bad & (1u << g)), "r"(pk.cmp + 8), "r"(pk.esc), "r"(pk.key | it << 9 | g << 7), "r"(a[4 * g + 3]),
                           "n"(ECAP), "r"((g < 2 ? d0 : d1) + (g & 1) * 8), "r"(a[4 * g]), "r"(a[4 * g + 1]), "r"(d2 + g * 4),
                           "r"(a[4 * g + 2]) : "memory");
        }
    }
    __syncwarp();
}
__device__ __forceinline__ void unpack16(uint32_t* a, uint32_t up, uint32_t c, int it, uint32_t flags, const Pack& pk) {
    const uint4 nn = lds128(c + 4096);
    const uint4 l0 = lds128(c), l1 = lds128(c + 2048);
    const uint32_t n[4] = {nn.x, nn.y, nn.z, nn.w};
    const uint32_t l[8] = {l0.x, l0.y, l0.z, l0.w, l1.x, l1.y, l1.z, l1.w};
#pragma unroll
    for (int g = 0; g < 4; g++) {
        const uint32_t h0 = n[g] & 0x87878787u, h1 = __funnelshift_r(n[g], n[g], 4) & 0x87878787u;
        a[4 * g]     = mul2(__byte_perm(l[2 * g], h0, 0x5140), up);
        a[4 * g + 1] = mul2(__byte_perm(l[2 * g], h0, 0x7362), up);
        a[4 * g + 2] = mul2(__byte_perm(l[2 * g + 1], h1, 0x5140), up);
        a[4 * g + 3] = mul2(__byte_perm(l[2 * g + 1], h1, 0x7362), up);
    }
    if (flags >> it & 1) {
        const uint32_t me = pk.key | it << 9;
        const uint2 e = lds64(pk.esc + min(me & 31u, ECAP - 1u) * 8);
        uint32_t hit = __ballot_sync(0xffffffffu, ((e.x ^ me) & ~0x19fu) == 0) & (uint32_t)((1ull << ECAP) - 1);
#pragma unroll 1
        while (hit) {
            const int src = __ffs(hit) - 1;
            hit &= hit - 1;
            const uint32_t d = __shfl_sync(0xffffffffu, e.x, src) ^ me, v = __shfl_sync(0xffffffffu, e.y, src);
            const uint32_t ge = (d >> 7) & 3;
            const uint2 r01 = lds64(c + (ge >> 1) * 2048 + (ge & 1) * 8);
            const uint32_t r2 = lds32(c + 4096 + ge * 4);
#pragma unroll
            for (int g = 0; g < 4; g++)
                if (d == (uint32_t)(g << 7)) { a[4 * g] = r01.x; a[4 * g + 1] = r01.y; a[4 * g + 2] = r2; a[4 * g + 3] = v; }
        }
    }
}

__device__ __forceinline__ void qk_half(float* s, float* s2, const uint32_t* a, uint32_t q) {
    const uint4 q0 = lds128(q), q1 = lds128(q + 256);
    mma(s, a, q0.x, q0.y);
    mma(s2, a + 4, q0.z, q0.w);
    mma(s, a + 8, q1.x, q1.y);
    mma(s2, a + 12, q1.z, q1.w);
}
__device__ __forceinline__ void pv_half(Acc& a, const uint32_t* f, uint32_t pa) {
    const uint32_t ones[4] = {0x3f803f80u, 0x3f803f80u, 0x3f803f80u, 0x3f803f80u};
    const uint4 pp = lds128(pa);
    mma(a.o[0], f, pp.x, pp.y);
    mma(a.o[1], f + 4, pp.x, pp.y);
    mma(a.l, ones, pp.x, pp.y);
    mma(a.o[0], f + 8, pp.z, pp.w);
    mma(a.o[1], f + 12, pp.z, pp.w);
    mma(a.l, ones, pp.z, pp.w);
}
__device__ __forceinline__ void load_khalf(uint32_t* a, uint32_t k) {
#pragma unroll
    for (int j = 0; j < 4; j++) ldsm4(a + j * 4, k ^ (j << 5));
    __syncwarp();
}
__device__ __forceinline__ void load_vhalf(uint32_t* f, uint32_t v) {
    ldsm4t(f, v);
    ldsm4t(f + 4, v ^ 32);
    ldsm4t(f + 8, v + 2048);
    ldsm4t(f + 12, (v ^ 32) + 2048);
    __syncwarp();
}
__device__ __forceinline__ void park(uint32_t* r, uint32_t kb, uint32_t vb) {
#pragma unroll
    for (int j = 0; j < 12; j++) {
        const int it = j / 3, c = j % 3;
        const uint32_t ad = it < 2 ? (kb ^ (c << 5)) + it * 8192 : (vb ^ ((c & 1) << 5)) + (c >> 1) * 2048 + (it - 2) * 4096;
        const uint4 u = lds128(ad);
        r[4 * j] = u.x; r[4 * j + 1] = u.y; r[4 * j + 2] = u.z; r[4 * j + 3] = u.w;
    }
}
__device__ __forceinline__ void unpark(const uint32_t* r, uint32_t c) {
#pragma unroll
    for (int j = 0; j < 12; j++) sts128(c + j * 2048, r[4 * j], r[4 * j + 1], r[4 * j + 2], r[4 * j + 3]);
}
__device__ __forceinline__ uint32_t k_offset(uint32_t slots, int wj, int lane) {
    const int row = wj * 16 + (lane & 7) + ((lane >> 3) & 1) * 8;
    return slots + row * 128 + (((lane >> 4) ^ (row & 7)) << 4);
}
__device__ __forceinline__ uint32_t v_offset(uint32_t slots, int wj, int lane) {
    const int key = (lane & 7) + (lane >> 4) * 8, cg = wj * 4 + ((lane >> 3) & 1);
    return slots + (cg >> 3) * 8192 + key * 128 + (((cg & 7) ^ (key & 7)) << 4);
}
__device__ __forceinline__ void load_kfrag(uint32_t* rk, uint32_t kb) {
#pragma unroll
    for (int ks = 0; ks < 8; ks++) ldsm4(rk + ks * 4, (kb ^ ((ks & 3) << 5)) + (ks >> 2) * 8192);
}

template <int NPRE>
__device__ __forceinline__ void ln_gemv_part(uint32_t (*f)[8], uint32_t a0, uint32_t a1, uint32_t kstride, uint32_t xw,
                                             int wq, int lane) {
    const int t = lane & 3, g = lane >> 2;
    float c0[4] = {0.f, 0.f, 0.f, 0.f}, c1[4] = {0.f, 0.f, 0.f, 0.f};
#pragma unroll
    for (int ks = 0; ks < 4; ks++) {
        uint32_t* ff = f[ks % NPRE];
        if (ks >= NPRE) {
            ldsm4t(ff, a0 + ks * kstride);
            ldsm4t(ff + 4, a1 + ks * kstride);
        }
        uint32_t xa = __shfl_sync(0xffffffffu, xw, ks * 8 + t), xb = __shfl_sync(0xffffffffu, xw, ks * 8 + 4 + t);
        if (g & 1) xa = xb = 0x3f803f80u;
        mma(c0, ff, xa, xb);
        mma(c1, ff + 4, xa, xb);
    }
    {
        const float a = bf_lo(xw), b = bf_hi(xw);
        const float su = a + b, sq = fmaf(a, a, b * b);
        float keep = (lane & 16) ? sq : su, send = (lane & 16) ? su : sq;
        keep += __shfl_xor_sync(0xffffffffu, send, 16);
#pragma unroll
        for (int k = 8; k > 0; k >>= 1) keep += __shfl_xor_sync(0xffffffffu, keep, k);
        if ((lane & 15) == 0) sts32(SM_RED + (lane >> 4) * 32 + wq * 4, __float_as_uint(keep));
    }
    float y = (t & 2) ? ((t & 1) ? c1[2] : c1[0]) : ((t & 1) ? c0[2] : c0[0]);
    float z = (t & 2) ? ((t & 1) ? c1[3] : c1[1]) : ((t & 1) ? c0[3] : c0[1]);
    sts64(SM_Q + wq * 256 + (t * 8 + g) * 8, __float_as_uint(y), __float_as_uint(z));
}
__device__ __forceinline__ float sum4(uint4 u) {
    return (__uint_as_float(u.x) + __uint_as_float(u.y)) + (__uint_as_float(u.z) + __uint_as_float(u.w));
}
__device__ __forceinline__ float ln_gemv_fin(int lane) {
    float mean, rstd;
    {
        const uint4 a = lds128(SM_RED), b = lds128(SM_RED + 16), c = lds128(SM_RED + 32), d = lds128(SM_RED + 48);
        mean = (sum4(a) + sum4(b)) * (1.f / 512.f);
        const float var = fmaxf(fmaf(sum4(c) + sum4(d), 1.f / 512.f, -mean * mean), 0.f) + 1e-5f;
        asm("rsqrt.approx.ftz.f32 %0, %1;" : "=f"(rstd) : "f"(var));
    }
    uint2 u[8];
#pragma unroll
    for (int j = 0; j < 8; j++) u[j] = lds64(SM_Q + j * 256 + lane * 8);
#define S8(f) (((__uint_as_float(u[0].f) + __uint_as_float(u[1].f)) + (__uint_as_float(u[2].f) + __uint_as_float(u[3].f))) + \
               ((__uint_as_float(u[4].f) + __uint_as_float(u[5].f)) + (__uint_as_float(u[6].f) + __uint_as_float(u[7].f))))
    return (S8(x) - mean * S8(y)) * rstd;
#undef S8
}
__device__ __forceinline__ void ar_add(uint4* dst, float y0, float y1) {
    asm volatile("red.relaxed.gpu.global.add.v4.f32 [%0], {%1, %2, %3, %1};" ::"l"(dst), "f"(1.f), "f"(y0), "f"(y1) : "memory");
}

__device__ __forceinline__ int unit_head(int cta, int wg) { return cta < 128 ? ((cta + (cta >> 3)) & 7) : (cta - 128) * 2 + wg; }
__device__ __forceinline__ int unit_index(int cta, int wg) { return cta < 128 ? (cta >> 3) * 2 + wg : 32; }
__device__ __forceinline__ void issue_item(int j, const Maps& tm, int tb, int ui, uint32_t slots, uint32_t bars) {
    const int slot = (int)((0x1010210432105432ull >> (4 * j)) & 15);
    tma_tile((j & 1) ? &tm.v : &tm.k, tb + (j >> 1) * NUNIT + ui, slots + slot * SLOT, bars + slot * 8);
}
__device__ __forceinline__ void load_ffn(const Maps& tm, int cta, int h, uint32_t z) {
    if (h) {
        tma_rows(&tm.wd, cta * 16, z, SM_WBAR);
    } else {
        expect_tx(SM_WBAR, SLOT);
        tma_2d(&tm.wu, cta * 16, 0, z, SM_WBAR);
        tma_2d(&tm.wu, cta * 16, 256, z + 8192, SM_WBAR);
    }
}
__device__ __forceinline__ void load_wq(const Maps& tm, int cta, int h, uint32_t z) {
    expect_tx(SM_WBAR, SLOT);
    tma_2d(&tm.wq, cta * 32, h * 256, z, SM_WBAR);
}
__device__ __forceinline__ void draw_ticket(uint32_t& ticket, const Params& p, int ph, int head, int lane) {
    asm volatile("{\n.reg .pred p;\nsetp.eq.u32 p, %2, 0;\n@p atom.relaxed.gpu.global.inc.u32 %0, [%1], 0xfffffffe;\n}"
                 : "+r"(ticket) : "l"(&g_s.ticket[ph][head][0]), "r"(lane) : "memory");
}
#define DESC(sk, sv) ((uint32_t)((sk) | ((sv) << 3) | 64))

__device__ __forceinline__ uint4* part_dst(const Params& p, int head, int ui, int tid) {
    const int lane = tid & 31, g = lane >> 2, t = lane & 3;
    return &g_s.part[(head * 4 + 2 * (t & 1) + (t >> 1)) * 4 + ((tid >> 5) & 3)][g >> 1][ui][g & 1];
}
__device__ __forceinline__ uint4* q_dst(const Params& p, int layer, int cta, int lane) {
    return &g_s.q[layer][(lane >> 3) & 1][cta >> 4][((cta & 3) * 16 + ((cta >> 2) & 3) * 4) * 2 + (lane & 7)];
}
__device__ __forceinline__ void publish_q(uint4* out, float r, uint32_t tag, int lane) {
    const int src = (lane & 1) * 16 + ((lane >> 1) & 3) * 2;
    const float q0 = __shfl_sync(0xffffffffu, r, src), q1 = __shfl_sync(0xffffffffu, r, src + 1);
    const float q2 = __shfl_sync(0xffffffffu, r, src + 8), q3 = __shfl_sync(0xffffffffu, r, src + 9);
    if (lane < 16) ll_st(out, pack_bf16(q0, q1), tag, pack_bf16(q2, q3), tag);
}

template <bool TAIL>
__device__ __forceinline__ void gemv_chain(const Maps& tm, const Params& p, const int cta, const uint32_t tag) {
    constexpr uint32_t Z_WO = SM_SLOTS + (TAIL ? 2 : 0) * SLOT, Z_GU = SM_SLOTS + (TAIL ? 3 : 0) * SLOT;
    [[maybe_unused]] constexpr int TB = TAIL ? 16 : 0;
    const int wq = __shfl_sync(0xffffffffu, tid_now() >> 5, 0);
    uint32_t xo;
    {
        const int lane = tid_now() & 31, g = lane >> 2, t = lane & 3;
        if (!TAIL) {
            const unsigned short* xp = reinterpret_cast<const unsigned short*>(p.x) + wq * 64 + t * 16 + g;
            xo = xp[0] | (uint32_t)xp[8] << 16;
            if (wq == 0 && lane < 16) ll_st(q_dst(p, 1, cta, lane), 0, 0, 0, 0);
            __syncwarp();
            if (wq == 1) l2_prefetch(&g_s.ar[0][0][0][0] + (cta & 63) * 128, 2048, POL_NORMAL);
        } else {
            unsigned long long u;
            uint32_t it = 0;
            do {
                spin_guard(it);
                asm volatile("ld.relaxed.gpu.global.b64 %0, [%1];" : "=l"(u) : "l"(&g_s.x2[wq * 32 + lane]) : "memory");
            } while (__any_sync(0xffffffffu, (uint32_t)(u >> 32) != tag - 1));
            xo = (uint32_t)u;
        }
        const uint32_t t16 = tag & 0xffffu;
        const uint4* src = &g_s.part[cta][wq][lane & 15][lane >> 4];
        const bool three = (lane & 15) == 0;
        if (wq == 0) {
            const uint32_t target = ((tag >> 2) * 2 + (TAIL ? 2 : 1)) * (2 * NCTA);
            uint32_t it = 0;
            bool pf = !TAIL;
            while (true) {
                uint32_t v;
                asm volatile("ld.acquire.gpu.global.u32 %0, [%1];" : "=r"(v) : "l"(&g_s.done[0]) : "memory");
                const int rem = __shfl_sync(0xffffffffu, (int)(target - v), 0);
                if (pf && rem <= PF_REM) {
                    pf = false;
                    l2_prefetch(p.wu + (size_t)cta * 14336, 14336, POL_FIRST);
                    l2_prefetch(p.wd + (size_t)cta * 14336, 14336, POL_FIRST);
                }
                if (rem <= 0) break;
                spin_guard(it);
                if (rem > 16) delay_cycles(400);
            }
        }
        __syncthreads();
        TS(TB + 14);
        uint4 a = ll_ld_last(src), b = ll_ld_last(src + 32), e = make_uint4(0, 0xff800000u | t16, 0, t16);
        if (three) e = ll_ld_last(src + 64);
        const uint32_t wa0 = Z_WO + wq * 2048 + ((lane & 7) + (lane >> 4) * 8) * 128 + ((((lane >> 3) & 1) ^ (lane & 7)) << 4);
        uint32_t f0[4][4], f1[4][4];
        mbar_wait(TAIL ? SM_TBAR : SM_WBAR, TAIL ? 0 : 1);
        __syncwarp();
        if (TAIL) {
#pragma unroll
            for (int mt = 0; mt < 4; mt++) {
                ldsm4t(f0[mt], wa0 ^ (mt << 5));
                ldsm4t(f1[mt], (wa0 ^ (mt << 5)) + USTR);
            }
        }
        {
            uint32_t it = 0;
            while (__any_sync(0xffffffffu, ((a.y ^ t16) | (a.w ^ t16) | (b.y ^ t16) | (b.w ^ t16) | (e.y ^ t16) | (e.w ^ t16)) << 16 != 0)) {
                spin_guard(it);
                a = ll_ld_last(src);
                b = ll_ld_last(src + 32);
                if (three) e = ll_ld_last(src + 64);
            }
        }
        TS(TB + 0);
        if (!TAIL && wq >= 6) l2_prefetch(p.wq + (size_t)(cta + (wq - 6) * 128) * 16384, 16384, POL_FIRST);
        const float la = __uint_as_float(__byte_perm(a.w, a.y, 0x7632)), lb = __uint_as_float(__byte_perm(b.w, b.y, 0x7632));
        const float le = __uint_as_float(__byte_perm(e.w, e.y, 0x7632));
        float mm;
        {
            int k = __float_as_int(fmaxf(fmaxf(la, lb), le));
            k ^= (k >> 31) & 0x7fffffff;
            k = __reduce_max_sync(0xffffffffu, k);
            k ^= (k >> 31) & 0x7fffffff;
            mm = __int_as_float(k);
        }
        const float wa = ex2(la - mm), wb = ex2(lb - mm), we = ex2(le - mm);
        const float v0 = fmaf(we, __uint_as_float(e.x), fmaf(wb, __uint_as_float(b.x), wa * __uint_as_float(a.x)));
        const float v1 = fmaf(we, __uint_as_float(e.z), fmaf(wb, __uint_as_float(b.z), wa * __uint_as_float(a.z)));
        float ws = wa + wb + we;
        float kk = (lane & 8) ? v1 : v0;
        kk += __shfl_xor_sync(0xffffffffu, (lane & 8) ? v0 : v1, 8);
        ws += __shfl_xor_sync(0xffffffffu, ws, 8);
        if (!TAIL) {
#pragma unroll
            for (int mt = 0; mt < S1_NPRE; mt++) {
                ldsm4t(f0[mt], wa0 ^ (mt << 5));
                ldsm4t(f1[mt], (wa0 ^ (mt << 5)) + USTR);
            }
        }
#pragma unroll
        for (int k = 4; k > 0; k >>= 1) {
            kk += __shfl_xor_sync(0xffffffffu, kk, k);
            ws += __shfl_xor_sync(0xffffffffu, ws, k);
        }
        {
            float r; asm("rcp.approx.ftz.f32 %0, %1;" : "=f"(r) : "f"(ws));
            const uint32_t o = pack_bf16(kk * r, 0.f);
            if ((lane & 7) == 0) sts16(SM_RED + 128 + (wq & 3) * 16 + (wq >> 2) * 8 + ((lane >> 3) & 1) * 4 + (lane >> 4) * 2, o);
        }
        uint4* out = &g_s.ar[TAIL ? 2 : 0][cta & 1][wq * 16 + (lane >> 1)][lane & 1];
        __syncthreads();
        TS(TB + 1);
        const uint4 ob = lds128(SM_RED + 128 + t * 16);
        float c0[4] = {0.f, 0.f, 0.f, 0.f}, c1[4] = {0.f, 0.f, 0.f, 0.f};
#pragma unroll
        for (int mt = 0; mt < 4; mt++) {
            constexpr int NP = TAIL ? 4 : S1_NPRE;
            uint32_t* g0 = f0[mt % NP];
            uint32_t* g1 = f1[mt % NP];
            if (mt >= NP) {
                ldsm4t(g0, wa0 ^ (mt << 5));
                ldsm4t(g1, (wa0 ^ (mt << 5)) + USTR);
            }
            const bool mine = (g >> 1) == mt;
            mma(c0, g0, mine ? ob.x : 0u, mine ? ob.y : 0u);
            mma(c1, g1, mine ? ob.z : 0u, mine ? ob.w : 0u);
        }
        ar_add(out, c0[0] + c1[0], c0[2] + c1[2]);
        TS(TB + 2);
        if (!TAIL) {
            if (wq == 4 || wq == 5) bar_sync(4, 256); else bar_arrive(4, 256);
        }
    }
#pragma unroll 1
    for (int hv = 0; hv < 2; hv++) {
        const int half = __shfl_sync(0xffffffffu, hv, 0);
        const bool ffn = cta < 112;
        if (TAIL && (half ? cta != 0 : !ffn)) break;
        uint32_t t0;
        asm volatile("mov.u32 %0, %%clock;" : "=r"(t0));
        const int lane = tid_now() & 31, g = lane >> 2, t = lane & 3;
        const bool qs = !TAIL && half;
        [[maybe_unused]] const int h = wq - 4;
        [[maybe_unused]] const uint32_t z = SM_SLOTS + h * USTR;
        if (!TAIL && (wq == 4 || wq == 5)) {
            if (!half) {
                if (ffn) load_ffn(tm, cta, h, z);
            } else if (!(WQ_EARLY && ffn && h == 0)) {
                if (!ffn) delay_cycles(D_SKIP);
                load_wq(tm, cta, h, z);
            }
        }
        constexpr int NPRE = TAIL ? 4 : MID_NPRE;
        uint32_t f[NPRE][8];
        const int row = (wq & 3) * 64 + (lane & 7) + (lane >> 4) * 8;
        const uint32_t a0 = qs ? SM_SLOTS + (wq >> 2) * USTR + row * 64 + ((((lane >> 3) & 1) ^ ((lane >> 1) & 3)) << 4)
                               : SM_WG + (wq >> 2) * 8192 + row * 32 + ((((lane >> 3) ^ (lane >> 2)) & 1) << 4);
        const uint32_t a1 = qs ? a0 ^ 32 : a0 - (SM_WG - Z_GU), kstride = qs ? 1024 : 512;
        {
            const uint4* src = &g_s.ar[(TAIL ? 2 : 0) + half][0][wq * 16 + (lane >> 1)][lane & 1];
            const uint32_t cnt = __float_as_uint(half ? 56.f : 64.f);
            if (TAIL && !half) {
                mbar_wait(SM_WBAR, 0);
                __syncwarp();
#pragma unroll
                for (int ks = 0; ks < NPRE; ks++) {
                    ldsm4t(f[ks], a0 + ks * kstride);
                    ldsm4t(f[ks] + 4, a1 + ks * kstride);
                }
            }
            {
                const uint32_t d = (half && !ffn) ? D_AR + D_SKIP : D_AR;
                uint32_t t1;
                do { asm volatile("mov.u32 %0, %%clock;" : "=r"(t1)); } while (t1 - t0 < d);
            }
            uint4 u, v;
            uint32_t it = 0;
            do {
                spin_guard(it);
                u = ll_ld(src);
                v = ll_ld(src + 1024);
            } while (__any_sync(0xffffffffu, u.x != cnt || u.w != cnt || v.x != cnt || v.w != cnt));
            const uint32_t y = pack_bf16(__uint_as_float(u.y) + __uint_as_float(v.y), __uint_as_float(u.z) + __uint_as_float(v.z));
            xo = pack_bf16(bf_lo(xo) + bf_lo(y), bf_hi(xo) + bf_hi(y));
        }
        if (half) TS(TB + 7); else TS(TB + 3);
        if (!half && !ffn) continue;
        const uint32_t xw = movm(xo);
        if (TAIL && half) {
            reinterpret_cast<uint32_t*>(p.out)[wq * 32 + lane] = xw;
            if (wq == 0) {
                if (lane < 16) g_s.ticket[lane >> 3][lane & 7][0] = 0;
                if (lane == 16) g_s.epoch = (tag >> 2) + 1;
            }
            break;
        }
        if (!TAIL) {
            mbar_wait(SM_WBAR, qs && ffn);
            __syncwarp();
#pragma unroll
            for (int ks = 0; ks < NPRE; ks++) {
                ldsm4t(f[ks], a0 + ks * kstride);
                ldsm4t(f[ks] + 4, a1 + ks * kstride);
            }
        }
        if (half) TS(8); else TS(TB + 4);
        ln_gemv_part<NPRE>(f, a0, a1, kstride, xw, wq, lane);
        const uint32_t wd0 = Z_GU + USTR + wq * 2048 + ((lane & 7) + (lane >> 4) * 8) * 128 + ((((lane >> 3) & 1) ^ (lane & 7)) << 4);
        uint32_t d[4][4];
        constexpr int DPRE = TAIL ? 4 : MID_DPRE;
#pragma unroll
        for (int mt = 0; mt < DPRE; mt++) ldsm4t(d[mt], wd0 ^ (mt << 5));
        uint4* out = qs ? q_dst(p, 1, cta, lane) : &g_s.ar[TAIL ? 3 : 1][cta & 1][wq * 16 + (lane >> 1)][lane & 1];
        __syncthreads();
        if (!half) TS(TB + 5);
        if (WQ_EARLY && !TAIL && !half && wq == 4) load_wq(tm, cta, 0, z);
        float r = ln_gemv_fin(lane);
        if (qs) {
            if (wq == 0) publish_q(out, r, tag, lane);
            if (cta == 0)
                asm volatile("st.relaxed.gpu.global.b64 [%0], %1;" ::"l"(&g_s.x2[wq * 32 + lane]), "l"((unsigned long long)tag << 32 | xo) : "memory");
            __syncthreads();
            TS(9);
            break;
        }
        r = bf16r(r);
        const float up = __shfl_down_sync(0xffffffffu, r, 16);
#pragma unroll
        for (int mt = DPRE; mt < 4; mt++) ldsm4t(d[mt], wd0 ^ (mt << 5));
        const float hh = (r > 0.f ? r : 0.f * r) * up;
        const float h0 = __shfl_sync(0xffffffffu, hh, 2 * t), h1 = __shfl_sync(0xffffffffu, hh, 2 * t + 1);
        const float h2 = __shfl_sync(0xffffffffu, hh, 2 * t + 8), h3 = __shfl_sync(0xffffffffu, hh, 2 * t + 9);
        const uint32_t b0 = pack_bf16(h0, h1), b1 = pack_bf16(h2, h3);
        float c0[4] = {0.f, 0.f, 0.f, 0.f}, c1[4] = {0.f, 0.f, 0.f, 0.f};
#pragma unroll
        for (int mt = 0; mt < 4; mt++) {
            const bool mine = (g >> 1) == mt;
            mma((mt & 1) ? c1 : c0, d[mt], mine ? b0 : 0u, mine ? b1 : 0u);
        }
        ar_add(out, c0[0] + c1[0], c0[2] + c1[2]);
        TS(TB + 6);
        if (!TAIL) {
            if (wq == 4 || wq == 5) bar_sync(4, 256); else bar_arrive(4, 256);
        }
    }
}

#define UVARS                                                                                               \
    const int wqu = __shfl_sync(0xffffffffu, tid_now() >> 5, 0);                                            \
    const int wg = wqu >> 2, wj = wqu & 3;                                                                  \
    [[maybe_unused]] const int head = unit_head(cta, wg), ui = unit_index(cta, wg), tb = head * NTILE;      \
    [[maybe_unused]] const uint32_t slots = SM_SLOTS + wg * USTR, bars = SM_BAR + wg * 48;                  \
    [[maybe_unused]] const int barid = 1 + wg;                                                              \
    [[maybe_unused]] const uint32_t qbase = cta < 128 ? SM_Q : SM_WG + wg * 1024;                           \
    [[maybe_unused]] const uint32_t rec = SM_ST + wg * 16;                                                  \
    [[maybe_unused]] const uint32_t mx = SM_MX + wg * 64;
#define Q_RD (qbase + (lane & 15) * 16)
#define P_RD (SM_P + wg * 512 + (lane & 15) * 16)
#define P_WR (SM_P + wg * 512 + (wj >> 1) * 256 + (wj & 1) * 8 + (lane & 15) * 16)

__device__ __forceinline__ void static_phase(const Maps& tm, const int cta, Acc& acc, uint32_t (*rp)[48]) {
    UVARS
#pragma unroll 1
    for (int rv = 0; rv < NSTAT; rv++) {
        const int rn = __shfl_sync(0xffffffffu, rv, 0);
        const int lane = tid_now() & 31;
        const uint32_t d = (uint32_t)(0x10210432105432ull >> (8 * rn)), par = 0x7c0u >> (2 * rn);
        const int sk = d & 7, sv = (d >> 4) & 7;
        Pack pk;
        pk.cmp = SM_CMP + wg * 32;
        pk.esc = SM_ESC + wg * (ECAP * 8);
        pk.key = (rn < 4 ? rn + 3 : 6 - rn) << 11 | wj << 5 | lane;
        const bool inplace = rn < 4;
        const uint32_t dst = slots + 2 * SLOT + (6 - rn) * 24576 + (wj * 32 + lane) * 16;
        const uint32_t kb = k_offset(slots, wj, lane) + sk * SLOT;
        float s[4] = {0.f, 0.f, 0.f, 0.f}, s2[4] = {0.f, 0.f, 0.f, 0.f};
        uint32_t a[16];
        mbar_wait(bars + sk * 8, par & 1);
        __syncwarp();
        {
            const uint32_t b4 = lds32(pk.cmp);
#pragma unroll SUNR
            for (int h = 0; h < 2; h++) {
                const uint32_t k = kb + h * 8192, e = dst + h * 6144;
                load_khalf(a, k);
                qk_half(s, s2, a, Q_RD + h * 512);
                pack16(a, b4, inplace ? k : e, inplace ? k ^ 32 : e + 2048, inplace ? k ^ 64 : e + 4096, h, pk);
            }
        }
#pragma unroll
        for (int i = 0; i < 4; i++) s[i] += s2[i];
        softmax_step(s, acc, P_WR, mx, barid, lane, wj);
        const uint32_t vb = v_offset(slots, wj, lane) + sv * SLOT;
        mbar_wait(bars + sv * 8, (par >> 1) & 1);
        __syncwarp();
        {
            const uint32_t b4 = lds32(pk.cmp + 4);
#pragma unroll SUNR
            for (int y = 0; y < 2; y++) {
                const uint32_t v = vb + y * 4096, e = dst + 12288 + y * 6144;
                load_vhalf(a, v);
                pv_half(acc, a, P_RD + y * 256);
                pack16(a, b4, inplace ? v : e, inplace ? v ^ 32 : e + 2048, inplace ? v + 2048 : e + 4096, 2 + y, pk);
            }
        }
        if (rn == 0) park(rp[0], kb, vb);
        if (rn == 1) park(rp[1], kb, vb);
        if (rn == 2) park(rp[2], kb, vb);
        if (rn == 3) park(rp[3], kb, vb);
        asm volatile("fence.proxy.async.shared::cta;" ::: "memory");
        wg_bar_or(barid, false);
        const int j = (int)((wj == 1 ? 0xe0c0a86u : 0xfd0b907u) >> (4 * rn)) & 15;
        if ((wj == 1 || wj == 2) && j) issue_item(j, tm, tb, ui, slots, bars);
        if (wj == 0) {
            const uint32_t st = lds32(rec + 4);
            if (lane == 0 && lds32(pk.cmp + 8) > ECAP) {
                sts16(SM_KEEP + wg * 64 + (st & 255) * 2, rn * NUNIT + ui);
                sts32(rec + 4, (st + 1) | 0x10000u << (pk.key >> 11));
            }
            __syncwarp();
        }
    }
    TSD(28);
    if (wqu == 0) __threadfence();
    wg_bar_or(barid, false);
}

__device__ __forceinline__ void acc_init(Acc& a) {
#pragma unroll
    for (int i = 0; i < 4; i++) { a.o[0][i] = 0.f; a.o[1][i] = 0.f; a.l[i] = 0.f; }
    a.m0 = a.m1 = __int_as_float(0xff800000);
}

__device__ __forceinline__ void attention_pass(const Maps& tm, const Params& p, const int cta, const int ph, const uint32_t tag0,
                                               Acc& acc, uint32_t (*rp)[48], float* s) {
    UVARS
    const int lim = ph ? T_KEEP0 : NTILE;
    uint32_t ticket = 0;
    if (wj == 0) draw_ticket(ticket, p, ph, head, tid_now() & 31);
    const uint32_t st0 = __shfl_sync(0xffffffffu, lds32(rec + 4), 0);
    uint32_t phbits = __shfl_sync(0xffffffffu, lds32(rec + 12), 0);
    int nk = st0 & 255;
    uint32_t cur = DESC(0, 1) | 256;
    uint32_t q0 = 0, q1 = 0;
    int rn = NSTAT, ki = 0, since = KRATIO;
    bool open = true;
    if (ph) {
        rn = 0; q0 = cur; cur = 128 | 8;
        if (nk > 0 && __shfl_sync(0xffffffffu, (int)lds16(SM_KEEP + wg * 64 + nk * 2 - 2), 0) >= T_KEEP0) nk--;
        else cur |= 512;
    }
#pragma unroll 1
    while (true) {
        const int lane = tid_now() & 31;
        const uint32_t rel = cur ? cur : (rn == 1 ? DESC(2, 3) : 0);
        const int sk = rel & 7, sv = (rel >> 3) & 7;
        const bool keeps = ph && ki < nk && (rel & 64);
        const bool want = (rel & 64) && open && (!(q0 & 256) || (keeps && since < KRATIO));
        int tkeep = 0;
        if (keeps) tkeep = __shfl_sync(0xffffffffu, lds16(SM_KEEP + wg * 64 + ki * 2), 0);
        const bool resid = rn + (cur == 0) < NSTAT;
#define PUBLISH()                                                                                                          \
        if (wj == 0) {                                                                                                     \
            uint32_t lb = 0;                                                                                               \
            if (resid && q0 && mbar_test(bars + ((q0 >> 3) & 7) * 8, (phbits >> ((q0 >> 3) & 7)) & 1)) lb = 0x10000u;      \
            asm volatile("{\n.reg .pred p, q;\n.reg .u32 w;\nmov.u32 w, %6;\nsetp.eq.u32 p, %7, 0;\n@p bra.uni N_%=;\n"  \
                         "shfl.sync.idx.b32 w, %1, 0, 31, 0xffffffff;\nadd.u32 w, w, %5;\nmin.u32 w, w, %6;\nN_%=:\n"      \
                         "setp.eq.u32 p, %2, 0;\nsetp.ge.and.u32 q, w, %3, p;\nor.b32 w, w, %8;\n@q or.b32 w, w, 0x20000;\n" \
                         "@p st.shared.u32 [%0], w;\n@q red.relaxed.gpu.global.add.u32 [%4], 1;\n}"                        \
                         ::"r"(rec), "r"(ticket), "r"(lane), "r"((!resid && !q0 && !keeps) ? lim : NTILE + 1),             \
                           "l"(&g_s.done[lane]), "n"(T_DYN0 + NUNIT), "n"(NTILE), "r"((uint32_t)want), "r"(lb) : "memory"); \
        }
        if (cur ? !(cur & 512) : !(st0 >> (16 + rn) & 1)) {
            Pack pk;
            pk.cmp = SM_CMP + wg * 32;
            pk.esc = SM_ESC + wg * (ECAP * 8);
            pk.key = rn << 11 | wj << 5 | lane;
            uint32_t a[16], vb, flags = 0;
            if (cur) {
                vb = v_offset(slots, wj, lane) + sv * SLOT;
                if (cur & 64) {
                    const uint32_t kb = k_offset(slots, wj, lane) + sk * SLOT;
                    float s2[4] = {0.f, 0.f, 0.f, 0.f};
                    s[0] = s[1] = s[2] = s[3] = 0.f;
                    mbar_wait(bars + sk * 8, (phbits >> sk) & 1);
                    __syncwarp();
                    if (DBG_U && ph == DBG_PH) TSW(26);
                    load_khalf(a, kb);
                    qk_half(s, s2, a, Q_RD);
                    load_khalf(a, kb + 8192);
                    qk_half(s, s2, a, Q_RD + 512);
                    mbar_wait(bars + sv * 8, (phbits >> sv) & 1);
                    __syncwarp();
                    phbits ^= 1u << sk | 1u << sv;
#pragma unroll
                    for (int i = 0; i < 4; i++) s[i] += s2[i];
                }
                load_vhalf(a, vb);
            } else {
                vb = slots + 2 * SLOT + min(rn, 2) * 24576 + (wj * 32 + lane) * 16;
                flags = lds32(pk.cmp + 16 + wj * 4) >> (rn * 4);
                if (rn == 3) unpark(rp[0], vb);
                if (rn == 4) unpark(rp[1], vb);
                if (rn == 5) unpark(rp[2], vb);
                if (rn == 6) unpark(rp[3], vb);
                const uint2 b4 = lds64(pk.cmp);
                float s2[4] = {0.f, 0.f, 0.f, 0.f};
                s[0] = s[1] = s[2] = s[3] = 0.f;
#pragma unroll RUNR
                for (int h = 0; h < 2; h++) {
                    unpack16(a, b4.x, vb + h * 6144, h, flags, pk);
                    qk_half(s, s2, a, Q_RD + h * 512);
                }
                unpack16(a, b4.y, vb + 12288, 2, flags, pk);
#pragma unroll
                for (int i = 0; i < 4; i++) s[i] += s2[i];
            }
            softmax_step(s, acc, P_WR, mx, barid, lane, wj);
            pv_half(acc, a, P_RD);
            if (cur) load_vhalf(a, vb + 4096);
            else unpack16(a, lds32(pk.cmp + 4), vb + 18432, 3, flags, pk);
            pv_half(acc, a, P_RD + 256);
        } else {
            wg_bar_or(barid, false);
        }
        PUBLISH();
        bar_sync(8 + wg, 128);
        const uint32_t w = __shfl_sync(0xffffffffu, lds32(rec), 0);
        if (w & 0x20000u) break;
        if (cur == 0) rn++;
        int tv = w & 0xffff;
        uint32_t push = 0;
        const bool streamed = tv < lim;
        if (streamed) push = (rel & 127) | 256;
        else if (keeps) { tv = tkeep; push = rel & 127; }
        else if (cur & 128) tv = T_DYN0 + ui;
        if (wj == 1 ? push != 0 : wj == 2 && (push | (cur & 128))) {
            const int sl = wj == 1 ? sk : sv;
            tma_tile(wj == 1 ? &tm.k : &tm.v, tb + tv, slots + sl * SLOT, bars + sl * 8);
            if (!ph && tv >= T_KEEP0 && tv < T_KEEPEND) l2_prefetch((wj == 1 ? p.k : p.v) + (size_t)(tb + tv) * SLOT, SLOT, POL_NORMAL);
        }
        if (streamed) {
            since++;

            if (!ph && tv >= T_KEEP0) {
                if (wj == 3 && lane == 0) sts16(SM_KEEP + wg * 64 + nk * 2, tv);
                nk++;
                if (nk >= KEEPCAP) open = false;
            }
            if (open && wj == 0) draw_ticket(ticket, p, ph, head, lane);
        } else {
            if (want) open = false;
            if (keeps) { ki++; since = 0; }
        }
        if (q0) q1 |= push; else q0 = push;
        if (resid && (q0 == 0 || (!(w & 0x10000u) && (rn < 2 || streamed)))) {
            cur = 0;
        } else {
            cur = q0; q0 = q1; q1 = 0;
        }
    }
    const int lane = tid_now() & 31;
    {
        const int e = (lane >> 1) & 1;
        float l = e ? acc.l[1] : acc.l[0], m = e ? acc.m1 : acc.m0;
        float inv; asm("rcp.approx.ftz.f32 %0, %1;" : "=f"(inv) : "f"(l));
        float lg; asm("lg2.approx.ftz.f32 %0, %1;" : "=f"(lg) : "f"(l));
        uint32_t lam = __float_as_uint(m + lg);
        const uint32_t t16 = (tag0 + ph + 1) & 0xffffu;
        uint32_t ta = (lam & 0xffff0000u) | t16, tc = (lam << 16) | t16;
        uint4* dst = part_dst(p, head, ui, wqu * 32 + lane);
        ll_st(dst, __float_as_uint((e ? acc.o[0][1] : acc.o[0][0]) * inv), ta,
                   __float_as_uint((e ? acc.o[0][3] : acc.o[0][2]) * inv), tc);
        ll_st(dst + 4 * NUNIT * 2, __float_as_uint((e ? acc.o[1][1] : acc.o[1][0]) * inv), ta,
                                   __float_as_uint((e ? acc.o[1][3] : acc.o[1][2]) * inv), tc);
    }
    if (ph) TSW(38); else TSW(36);
    if (wj == 0 && lane == 0) {
        sts32(rec + 4, nk | (st0 & 0xffff0000u));
        sts32(rec + 12, phbits);
    }
}

__global__ void __launch_bounds__(256, 1)
fused_kernel(const __grid_constant__ Maps tm, const Params p) {
    extern __shared__ __align__(1024) unsigned char smem_raw[];
    const int cta = blockIdx.x;
    const bool worker = cta < 128;
    uint32_t tag0;
    if ((uint32_t)__cvta_generic_to_shared(smem_raw) != SM_BASE) __trap();
    TS(40);
    uint32_t rp[4][48];
    Acc acc;
    {
        UVARS
        const int lane = tid_now() & 31;
        if (wj == 0) {
#pragma unroll
            for (int i = 0; i < 6; i++) mbar_init(bars + i * 8, 1);
            mbar_init(SM_WBAR + wg * 8, 2);
            mbar_init(SM_DBAR + wg * 8, 1);
            asm volatile("fence.proxy.async.shared::cta;" ::: "memory");
            __syncwarp();
            if (worker && wg == 0) {
                load_wq(tm, cta, 0, SM_SLOTS + SLOT);
                load_wq(tm, cta, 1, SM_SLOTS + USTR + SLOT);
            }
            issue_item(0, tm, tb, ui, slots, bars);
            issue_item(1, tm, tb, ui, slots, bars);
            if (worker && wg == 0 && lane < 16) ll_st(q_dst(p, 0, cta, lane), 0, 0, 0, 0);
        }
        if (wj == 1) {
            if (lane < ECAP) sts64(SM_ESC + wg * (ECAP * 8) + lane * 8, 0xffffffffu, 0);
            if (lane < 8) sts32(SM_CMP + wg * 32 + lane * 4, 0);
            if (lane < 4) sts32(rec + lane * 4, lane == 3 ? 0x27 : 0);
        }
        if (wj == 2) {
            const uint4 u = *reinterpret_cast<const uint4*>(p.x + wg * 256 + lane * 8);
            sts128(SM_P + wg * 512 + lane * 16, u.x, u.y, u.z, u.w);
        }
        if (wqu == 7 && worker && lane < 16) ll_st(&g_s.ar[0][0][0][0] + (cta * 8 + (lane >> 1)) * 8 + (lane & 1), 0, 0, 0, 0);
        if (wqu == 3) {
            uint32_t e;
            asm volatile("ld.relaxed.gpu.global.u32 %0, [%1];" : "=r"(e) : "l"(&g_s.epoch) : "memory");
            sts32(SM_RED, e * 4 + 1);
        }
        __syncthreads();
        tag0 = __shfl_sync(0xffffffffu, lds32(SM_RED), 0);
        const uint32_t xw = lds32(SM_P + wqu * 128 + lane * 4);
        __syncthreads();
        uint32_t it = 0;
        int item = 2;
#pragma unroll 1
        for (int stage = worker ? 0 : 1; stage < 3 || item < 6;) {
            if (item < (stage ? 6 : 5) && (wj != 1 || stage == 3 || mbar_test(bars + item * 8, 0))) {
                if (wj == 1) issue_item(item, tm, tb, ui, slots, bars);
                item++;
                continue;
            }
            spin_guard(it);
            if (stage == 0) {
                if (!mbar_test(SM_WBAR, 0)) continue;
                TS(32);
                const int row = wj * 64 + (lane & 7) + (lane >> 4) * 8;
                const uint32_t a0 = slots + SLOT + row * 64 + ((((lane >> 3) & 1) ^ ((lane >> 1) & 3)) << 4);
                uint32_t f[1][8];
                ldsm4t(f[0], a0);
                ldsm4t(f[0] + 4, a0 ^ 32);
                ln_gemv_part<1>(f, a0, a0 ^ 32, 1024, xw, wqu, lane);
                __syncthreads();
                if (wqu == 0) publish_q(q_dst(p, 0, cta, lane), ln_gemv_fin(lane), tag0, lane);
                if (wqu == 6 && cta < 112) {
                    expect_tx(SM_DBAR, SLOT);
                    tma_2d(&tm.wg, cta * 16, 0, SM_WG, SM_DBAR);
                    tma_2d(&tm.wg, cta * 16, 256, SM_WG + 8192, SM_DBAR);
                }
                __syncthreads();
                TS(33);
            } else if (stage == 1) {
                if (!mbar_test(bars + 2 * 8, 0) || !mbar_test(bars + 3 * 8, 0)) continue;
#pragma unroll 1
                for (int h = 0; h < 4; h++) {
                    uint32_t r[16], m = 0;
                    load_khalf(r, k_offset(slots, wj, lane) + 2 * SLOT + h * 8192);
#pragma unroll
                    for (int j = 0; j < 16; j++) m = __vmaxu2(m, r[j] & 0x7fff7fffu);
                    m = __reduce_max_sync(0xffffffffu, max(m >> 23, (m >> 7) & 0xffu));
                    if (lane == 0)
                        asm volatile("red.shared.max.u32 [%0], %1;" ::"r"(SM_CMP + wg * 32 + (h & 2) * 2),
                                     "r"((min(max(m, 15u), 141u) + 112u) * 0x00800080u) : "memory");
                    __syncwarp();
                }
            } else {
                const uint4 v = ll_ld(&g_s.q[0][cta >> 7][head][wj * 32 + lane]);
                if (__any_sync(0xffffffffu, v.y != tag0 || v.w != tag0)) { delay_cycles(200); continue; }
                sts64(qbase + (wj * 32 + lane) * 8, v.x, v.z);
            }
            stage++;
        }
        wg_bar_or(barid, false);
        TS(34);
#pragma unroll
        for (int i = 0; i < 4; i++)
#pragma unroll
            for (int j = 0; j < 48; j++) asm volatile("" : "=r"(rp[i][j]));
        acc_init(acc);
    }
    static_phase(tm, cta, acc, rp);
    float s[4] = {0.f, 0.f, 0.f, 0.f};
#pragma unroll 1
    for (int phv = 0;; phv = 1) {
        const int ph = __shfl_sync(0xffffffffu, phv, 0);
        attention_pass(tm, p, cta, ph, tag0, acc, rp, s);
        if (ph) break;
        uint32_t rx[32];
        {
            UVARS
            load_kfrag(rx, k_offset(slots, wj, tid_now() & 31));
            wg_bar_or(barid, false);
            if (worker && wj == 3) tma_rows(&tm.wo, cta * 32 + wg * 16, slots, SM_WBAR);
            if (cta < 112) mbar_wait(SM_DBAR, 0);
            __syncwarp();
        }
        if (worker) gemv_chain<false>(tm, p, cta, tag0 + 1);
        UVARS
        const int lane = tid_now() & 31;
        const uint4* src = &g_s.q[1][cta >> 7][head][wj * 32 + lane];
        uint4 v;
        uint32_t it = 0;
        do {
            spin_guard(it);
            if (it == 1 || !worker) delay_cycles(D_AG);
            v = ll_ld(src);
            if (it == 1 && wj == 1) tma_tile(&tm.k, tb + T_DYN0 + ui, slots, bars);
        } while (__any_sync(0xffffffffu, v.y != tag0 + 1 || v.w != tag0 + 1));
        sts64(qbase + (wj * 32 + lane) * 8, v.x, v.z);
        wg_bar_or(barid, false);
        TS(10);
        float s2[4] = {0.f, 0.f, 0.f, 0.f};
        s[0] = s[1] = s[2] = s[3] = 0.f;
        qk_half(s, s2, rx, Q_RD);
        qk_half(s, s2, rx + 16, Q_RD + 512);
#pragma unroll
        for (int i = 0; i < 4; i++) s[i] += s2[i];
        acc_init(acc);
    }
    if (worker) {
        UVARS
        if (wj == 3) tma_rows(&tm.wo, cta * 32 + wg * 16, slots + 2 * SLOT, SM_TBAR);
        if (wj == 2 && cta < 112) load_ffn(tm, cta, wg, slots + 3 * SLOT);
        gemv_chain<true>(tm, p, cta, tag0 + 2);
    }
}

typedef CUresult (*EncodeFn)(CUtensorMap*, CUtensorMapDataType, cuuint32_t, void*, const cuuint64_t*, const cuuint64_t*,
                             const cuuint32_t*, const cuuint32_t*, CUtensorMapInterleave, CUtensorMapSwizzle,
                             CUtensorMapL2promotion, CUtensorMapFloatOOBfill);

void make_map(EncodeFn encode, CUtensorMap* m, void* base, int rank, const cuuint64_t* gd, const cuuint64_t* gs,
              const cuuint32_t* bx, CUtensorMapSwizzle sw) {
    const cuuint32_t es[3] = {1, 1, 1};
    encode(m, CU_TENSOR_MAP_DATA_TYPE_BFLOAT16, rank, base, gd, gs, bx, es, CU_TENSOR_MAP_INTERLEAVE_NONE, sw,
           CU_TENSOR_MAP_L2_PROMOTION_NONE, CU_TENSOR_MAP_FLOAT_OOB_FILL_NONE);
}

}

extern "C" void kernel_launch(void* const* d_in, const int* in_sizes, int n_in, void* d_out, int out_size) {
    (void)in_sizes; (void)n_in; (void)out_size;
    static EncodeFn encode = nullptr;
    static void* scratch = nullptr;
    if (!encode) {
        void* fn = nullptr;
        cudaDriverEntryPointQueryResult qr;
        cudaGetDriverEntryPoint("cuTensorMapEncodeTiled", &fn, cudaEnableDefault, &qr);
        encode = (EncodeFn)fn;
        cudaGetSymbolAddress(&scratch, g_scratch);
        cudaFuncSetAttribute(fused_kernel, cudaFuncAttributeMaxDynamicSharedMemorySize, SM_TOTAL);
    }
    Maps tm;
    {
        const cuuint64_t gd[3] = {64, 8ull * 65536ull, 2}, gs[2] = {256, 128};
        const cuuint32_t bx[3] = {64, 64, 2};
        make_map(encode, &tm.k, d_in[1], 3, gd, gs, bx, CU_TENSOR_MAP_SWIZZLE_128B);
        make_map(encode, &tm.v, d_in[2], 3, gd, gs, bx, CU_TENSOR_MAP_SWIZZLE_128B);
    }
    {
        const cuuint64_t gd[2] = {4096, 512}, gs[1] = {8192};
        const cuuint32_t bx[2] = {32, 256};
        make_map(encode, &tm.wq, d_in[3], 2, gd, gs, bx, CU_TENSOR_MAP_SWIZZLE_64B);
    }
    {
        const cuuint64_t gd[3] = {64, 4096, 8}, gs[2] = {1024, 128};
        const cuuint32_t bx[3] = {64, 16, 8};
        make_map(encode, &tm.wo, d_in[4], 3, gd, gs, bx, CU_TENSOR_MAP_SWIZZLE_128B);
        const cuuint64_t gd2[3] = {64, 1792, 8};
        make_map(encode, &tm.wd, d_in[8], 3, gd2, gs, bx, CU_TENSOR_MAP_SWIZZLE_128B);
    }
    {
        const cuuint64_t gd[2] = {1792, 512}, gs[1] = {3584};
        const cuuint32_t bx[2] = {16, 256};
        make_map(encode, &tm.wg, d_in[6], 2, gd, gs, bx, CU_TENSOR_MAP_SWIZZLE_32B);
        make_map(encode, &tm.wu, d_in[7], 2, gd, gs, bx, CU_TENSOR_MAP_SWIZZLE_32B);
    }
    Params p;
    p.x = (const __nv_bfloat16*)d_in[0];
    p.k = (const char*)d_in[1];
    p.v = (const char*)d_in[2];
    p.wq = (const char*)d_in[3];
    p.wo = (const char*)d_in[4];
    p.wg = (const char*)d_in[6];
    p.wu = (const char*)d_in[7];
    p.wd = (const char*)d_in[8];
    p.out = (__nv_bfloat16*)d_out;
    p.s = (Scratch*)scratch;
    fused_kernel<<<NCTA, 256, SM_TOTAL, cudaStreamPerThread>>>(tm, p);
}
```

```cpp
#include <cuda_runtime.h>
#include <cuda_bf16.h>
#include <cuda.h>
#include <stdint.h>

namespace {

constexpr int NCTA      = 132;
constexpr int NUNIT     = 33;
constexpr int NTILE     = 1024;
constexpr int SLOT      = 16384;
constexpr int NSTAT     = 7;
constexpr int T_DYN0    = NSTAT * NUNIT;
#define NKEEP 198
#define KEEP_TAILSKIP 33
#define KRATIO 1
#define D_AR 650
#define D_SKIP 1500
#define WQ_EARLY 1
#define D_AG 200
#define PF_REM 0
#define RUNROLL 1
#define SUNROLL 1
#define MID_NPRE 2
#define S1_NPRE 2
#define MID_DPRE 0
#define ECAP 28
#define DBG_U 0
#define DBG_PH 0
constexpr int T_KEEP0   = NTILE - NKEEP;
constexpr int T_KEEPEND = NTILE - KEEP_TAILSKIP;
constexpr int SUNR      = SUNROLL, RUNR = RUNROLL;
constexpr int KEEPCAP   = 32;
constexpr unsigned SPIN_LIMIT = 1u << 22;

constexpr uint32_t SM_BASE  = 1024;
constexpr uint32_t USTR     = 2 * SLOT + 3 * 24576;
constexpr uint32_t SM_SLOTS = SM_BASE;
constexpr uint32_t SM_WG    = SM_SLOTS + 2 * USTR;
constexpr uint32_t SM_Q     = SM_WG + SLOT;
constexpr uint32_t SM_P     = SM_Q + 1024;
constexpr uint32_t SM_RED   = SM_P + 1024;
constexpr uint32_t SM_MX    = SM_RED;
constexpr uint32_t SM_BAR   = SM_RED + 192;
constexpr uint32_t SM_WBAR  = SM_BAR + 96;
constexpr uint32_t SM_TBAR  = SM_BAR + 104;
constexpr uint32_t SM_DBAR  = SM_BAR + 112;
constexpr uint32_t SM_KEEP  = SM_BAR + 128;
constexpr uint32_t SM_ST    = SM_KEEP + 128;
constexpr uint32_t SM_CMP   = SM_ST + 32;
constexpr uint32_t SM_ESC   = SM_CMP + 32;
constexpr int SM_TOTAL      = SM_ESC + 2 * ECAP * 8 - SM_BASE;
static_assert(SM_TOTAL <= 232448 && ECAP <= 32, "smem");

struct Scratch {
    uint4 part[128][8][NUNIT][2];
    uint4 ar[4][2][128][8];
    uint2 x2[256];
    uint4 q[2][2][8][128];
    unsigned ticket[2][8][32];
    unsigned done[32];
    unsigned epoch;
};
__device__ Scratch g_scratch;
#define g_s (*p.s)
#define TS(i)
#define TSD(i)
#define TSW(i)
#define TT(ph, head, tile)

struct Maps { CUtensorMap k, v, wq, wo, wg, wu, wd; };
struct Params {
    const __nv_bfloat16* x;
    const char* k;
    const char* v;
    const char* wq;
    const char* wo;
    const char* wg;
    const char* wu;
    const char* wd;
    __nv_bfloat16* out;
    Scratch* s;
};

__device__ __forceinline__ void mbar_init(uint32_t bar, uint32_t cnt) {
    asm volatile("{\n.reg .pred p;\nelect.sync _|p, 0xffffffff;\n@p mbarrier.init.shared::cta.b64 [%0], %1;\n}" ::"r"(bar), "r"(cnt) : "memory");
}
__device__ __forceinline__ void mbar_wait(uint32_t bar, uint32_t parity) {
    asm volatile("{\n.reg .pred p, q;\n.reg .u32 c;\n"
                 "mbarrier.try_wait.parity.shared::cta.b64 p, [%0], %1;\n@p bra D_%=;\nmov.u32 c, 0;\n"
                 "W_%=:\nmbarrier.try_wait.parity.shared::cta.b64 p, [%0], %1;\nadd.u32 c, c, 1;\n"
                 "setp.lt.and.u32 q, c, %2, !p;\n@q bra W_%=;\n@!p trap;\nD_%=:\n}"
                 ::"r"(bar), "r"(parity), "n"(SPIN_LIMIT) : "memory");
}
__device__ __forceinline__ void spin_guard(uint32_t& it) {
    asm volatile("{\n.reg .pred q;\nadd.u32 %0, %0, 1;\nsetp.gt.u32 q, %0, %1;\n@q trap;\n}" : "+r"(it) : "n"(SPIN_LIMIT));
}
constexpr uint64_t POL_FIRST = 0x12f0000000000000ull, POL_NORMAL = 0x16f0000000000000ull;
__device__ __forceinline__ void tma_rows(const CUtensorMap* tm, int row, uint32_t dst, uint32_t bar) {
    asm volatile("{\n.reg .pred p;\nelect.sync _|p, 0xffffffff;\n"
                 "@p mbarrier.arrive.expect_tx.shared::cta.b64 _, [%4], %6;\n"
                 "@p cp.async.bulk.tensor.3d.shared::cluster.global.mbarrier::complete_tx::bytes.L2::cache_hint "
                 "[%0], [%1, {%2, %3, %2}], [%4], %5;\n}"
                 ::"r"(dst), "l"(tm), "r"(0), "r"(row), "r"(bar), "l"(POL_FIRST), "r"(SLOT) : "memory");
}
__device__ __forceinline__ void tma_tile(const CUtensorMap* tm, int gtile, uint32_t dst, uint32_t bar) {
    tma_rows(tm, gtile * 64, dst, bar);
}
__device__ __forceinline__ void expect_tx(uint32_t bar, uint32_t bytes) {
    asm volatile("{\n.reg .pred p;\nelect.sync _|p, 0xffffffff;\n@p mbarrier.arrive.expect_tx.shared::cta.b64 _, [%0], %1;\n}"
                 ::"r"(bar), "r"(bytes) : "memory");
}
__device__ __forceinline__ void tma_2d(const CUtensorMap* tm, int c0, int c1, uint32_t dst, uint32_t bar) {
    asm volatile("{\n.reg .pred p;\nelect.sync _|p, 0xffffffff;\n"
                 "@p cp.async.bulk.tensor.2d.shared::cluster.global.mbarrier::complete_tx::bytes.L2::cache_hint "
                 "[%0], [%1, {%2, %3}], [%4], %5;\n}"
                 ::"r"(dst), "l"(tm), "r"(c0), "r"(c1), "r"(bar), "l"(POL_FIRST) : "memory");
}
__device__ __forceinline__ void l2_prefetch(const void* p, uint32_t bytes, uint64_t pol) {
    asm volatile("{\n.reg .pred p;\nelect.sync _|p, 0xffffffff;\n"
                 "@p cp.async.bulk.prefetch.L2.global.L2::cache_hint [%0], %1, %2;\n}" ::"l"(p), "r"(bytes), "l"(pol) : "memory");
}
__device__ __forceinline__ void ldsm4(uint32_t* r, uint32_t a) {
    asm volatile("ldmatrix.sync.aligned.m8n8.x4.shared.b16 {%0,%1,%2,%3}, [%4];"
                 : "=r"(r[0]), "=r"(r[1]), "=r"(r[2]), "=r"(r[3]) : "r"(a) : "memory");
}
__device__ __forceinline__ void ldsm4t(uint32_t* r, uint32_t a) {
    asm volatile("ldmatrix.sync.aligned.m8n8.x4.trans.shared.b16 {%0,%1,%2,%3}, [%4];"
                 : "=r"(r[0]), "=r"(r[1]), "=r"(r[2]), "=r"(r[3]) : "r"(a) : "memory");
}
__device__ __forceinline__ void mma(float* c, const uint32_t* a, uint32_t b0, uint32_t b1) {
    asm volatile("mma.sync.aligned.m16n8k16.row.col.f32.bf16.bf16.f32 {%0,%1,%2,%3}, {%4,%5,%6,%7}, {%8,%9}, {%0,%1,%2,%3};"
                 : "+f"(c[0]), "+f"(c[1]), "+f"(c[2]), "+f"(c[3])
                 : "r"(a[0]), "r"(a[1]), "r"(a[2]), "r"(a[3]), "r"(b0), "r"(b1));
}
__device__ __forceinline__ uint32_t movm(uint32_t a) {
    uint32_t d; asm volatile("movmatrix.sync.aligned.m8n8.trans.b16 %0, %1;" : "=r"(d) : "r"(a)); return d;
}
__device__ __forceinline__ uint32_t pack_bf16(float lo, float hi) {
    uint32_t d; asm("cvt.rn.bf16x2.f32 %0, %1, %2;" : "=r"(d) : "f"(hi), "f"(lo)); return d;
}
__device__ __forceinline__ float bf16r(float v) { return __uint_as_float(pack_bf16(v, 0.f) << 16); }
__device__ __forceinline__ float bf_lo(uint32_t w) { return __uint_as_float(w << 16); }
__device__ __forceinline__ float bf_hi(uint32_t w) { return __uint_as_float(w & 0xffff0000u); }
__device__ __forceinline__ float ex2(float v) { float d; asm("ex2.approx.ftz.f32 %0, %1;" : "=f"(d) : "f"(v)); return d; }
__device__ __forceinline__ uint4 lds128(uint32_t a) {
    uint4 v; asm volatile("ld.shared.v4.u32 {%0,%1,%2,%3}, [%4];" : "=r"(v.x), "=r"(v.y), "=r"(v.z), "=r"(v.w) : "r"(a) : "memory"); return v;
}
__device__ __forceinline__ uint2 lds64(uint32_t a) {
    uint2 v; asm volatile("ld.shared.v2.u32 {%0,%1}, [%2];" : "=r"(v.x), "=r"(v.y) : "r"(a) : "memory"); return v;
}
__device__ __forceinline__ uint32_t lds32(uint32_t a) {
    uint32_t v; asm volatile("ld.shared.u32 %0, [%1];" : "=r"(v) : "r"(a) : "memory"); return v;
}
__device__ __forceinline__ void sts128(uint32_t a, uint32_t x, uint32_t y, uint32_t z, uint32_t w) {
    asm volatile("st.shared.v4.u32 [%0], {%1,%2,%3,%4};" ::"r"(a), "r"(x), "r"(y), "r"(z), "r"(w) : "memory");
}
__device__ __forceinline__ void sts64(uint32_t a, uint32_t x, uint32_t y) {
    asm volatile("st.shared.v2.u32 [%0], {%1,%2};" ::"r"(a), "r"(x), "r"(y) : "memory");
}
__device__ __forceinline__ void sts32(uint32_t a, uint32_t x) {
    asm volatile("st.shared.u32 [%0], %1;" ::"r"(a), "r"(x) : "memory");
}
__device__ __forceinline__ void sts16(uint32_t a, uint32_t x) {
    asm volatile("st.shared.u16 [%0], %1;" ::"r"(a), "h"((unsigned short)x) : "memory");
}
__device__ __forceinline__ uint32_t lds16(uint32_t a) {
    unsigned short v; asm volatile("ld.shared.u16 %0, [%1];" : "=h"(v) : "r"(a) : "memory"); return v;
}
__device__ __forceinline__ bool wg_bar_or(int id, bool p) {
    uint32_t r;
    asm volatile("{\n.reg .pred a, b;\nsetp.ne.u32 a, %2, 0;\nbar.red.or.pred b, %1, 128, a;\nselp.u32 %0, 1, 0, b;\n}"
                 : "=r"(r) : "r"(id), "r"((uint32_t)p) : "memory");
    return r != 0;
}
__device__ __forceinline__ uint4 ll_ld(const uint4* p) {
    unsigned long long a, b;
    asm volatile("ld.relaxed.gpu.global.v2.b64 {%0,%1}, [%2];" : "=l"(a), "=l"(b) : "l"(p) : "memory");
    return make_uint4((uint32_t)a, (uint32_t)(a >> 32), (uint32_t)b, (uint32_t)(b >> 32));
}
__device__ __forceinline__ void ll_st(uint4* p, uint32_t v0, uint32_t t0, uint32_t v1, uint32_t t1) {
    unsigned long long a = ((unsigned long long)t0 << 32) | v0, b = ((unsigned long long)t1 << 32) | v1;
    asm volatile("st.relaxed.gpu.global.v2.b64 [%0], {%1,%2};" ::"l"(p), "l"(a), "l"(b) : "memory");
}
__device__ __forceinline__ uint4 ll_ld_last(const uint4* p) {
    unsigned long long a, b;
    asm volatile("ld.relaxed.gpu.global.L2::cache_hint.v2.b64 {%0,%1}, [%2], %3;" : "=l"(a), "=l"(b) : "l"(p), "l"(POL_FIRST) : "memory");
    return make_uint4((uint32_t)a, (uint32_t)(a >> 32), (uint32_t)b, (uint32_t)(b >> 32));
}
__device__ __forceinline__ void bar_sync(int id, int n) { asm volatile("bar.sync %0, %1;" ::"r"(id), "r"(n) : "memory"); }
__device__ __forceinline__ void bar_arrive(int id, int n) { asm volatile("bar.arrive %0, %1;" ::"r"(id), "r"(n) : "memory"); }
__device__ __forceinline__ void delay_cycles(int n) {
    if (n > 0) {
        uint32_t t0, t1;
        asm volatile("mov.u32 %0, %%clock;" : "=r"(t0));
        do { asm volatile("mov.u32 %0, %%clock;" : "=r"(t1)); } while (t1 - t0 < (uint32_t)n);
    }
}
__device__ __forceinline__ int tid_now() {
    int t; asm volatile("mov.u32 %0, %%tid.x;" : "=r"(t)); return t;
}
__device__ __forceinline__ bool mbar_test(uint32_t bar, uint32_t parity) {
    uint32_t ok;
    asm volatile("{\n.reg .pred p;\nmbarrier.test_wait.parity.shared::cta.b64 p, [%1], %2;\nselp.u32 %0, 1, 0, p;\n}"
                 : "=r"(ok) : "r"(bar), "r"(parity) : "memory");
    return ok != 0;
}

struct Acc {
    float o[2][4];
    float l[4];
    float m0, m1;
};

constexpr float SCALE_LOG2 = 0.08838834764831845f * 1.4426950408889634f;

__device__ __forceinline__ void softmax_step(float* s, Acc& a, uint32_t p_wr, uint32_t mx, int barid, int lane, int wj) {
#pragma unroll
    for (int i = 0; i < 4; i++) s[i] *= SCALE_LOG2;
    bool over = fmaxf(s[0], s[2]) > a.m0 || fmaxf(s[1], s[3]) > a.m1;
    {
        uint32_t b0 = movm(pack_bf16(ex2(s[0] - a.m0), ex2(s[1] - a.m1)));
        uint32_t b1 = movm(pack_bf16(ex2(s[2] - a.m0), ex2(s[3] - a.m1)));
        if (lane < 16) sts64(p_wr, b0, b1);
    }
    if (wg_bar_or(barid, over)) {
        float x0 = fmaxf(s[0], s[2]), x1 = fmaxf(s[1], s[3]);
#pragma unroll
        for (int d = 4; d < 32; d <<= 1) {
            x0 = fmaxf(x0, __shfl_xor_sync(0xffffffffu, x0, d));
            x1 = fmaxf(x1, __shfl_xor_sync(0xffffffffu, x1, d));
        }
        if (lane < 2) sts64(mx + wj * 16 + lane * 8, __float_as_uint(x0), __float_as_uint(x1));
        wg_bar_or(barid, false);
        float n0 = a.m0, n1 = a.m1;
#pragma unroll
        for (int j = 0; j < 4; j++) {
            uint2 v = lds64(mx + j * 16 + (lane & 1) * 8);
            n0 = fmaxf(n0, __uint_as_float(v.x));
            n1 = fmaxf(n1, __uint_as_float(v.y));
        }
        float f0 = ex2(a.m0 - n0), f1 = ex2(a.m1 - n1);
        a.m0 = n0; a.m1 = n1;
        a.o[0][0] *= f0; a.o[0][2] *= f0; a.o[1][0] *= f0; a.o[1][2] *= f0; a.l[0] *= f0; a.l[2] *= f0;
        a.o[0][1] *= f1; a.o[0][3] *= f1; a.o[1][1] *= f1; a.o[1][3] *= f1; a.l[1] *= f1; a.l[3] *= f1;
        uint32_t b0 = movm(pack_bf16(ex2(s[0] - n0), ex2(s[1] - n1)));
        uint32_t b1 = movm(pack_bf16(ex2(s[2] - n0), ex2(s[3] - n1)));
        if (lane < 16) sts64(p_wr, b0, b1);
        wg_bar_or(barid, false);
    }
}

__device__ __forceinline__ uint32_t mul2(uint32_t a, uint32_t b) {
    uint32_t d; asm("mul.rn.bf16x2 %0, %1, %2;" : "=r"(d) : "r"(a), "r"(b)); return d;
}
struct Pack {
    uint32_t cmp;
    uint32_t esc;
    uint32_t key;
};
__device__ __forceinline__ void pack16(const uint32_t* a, uint32_t up, uint32_t d0, uint32_t d1, uint32_t d2, int it,
                                       const Pack& pk) {
    const uint32_t dn = 0x7f007f00u - up;
    uint32_t l[8], n[4], bad = 0;
#pragma unroll
    for (int g = 0; g < 4; g++) {
        uint32_t z[4], e = 0;
#pragma unroll
        for (int j = 0; j < 4; j++) {
            z[j] = mul2(a[4 * g + j], dn);
            e |= mul2(z[j], up) ^ a[4 * g + j];
        }
        const uint32_t x0 = __byte_perm(z[0], z[1], 0x7531), x1 = __byte_perm(z[2], z[3], 0x7531);
        l[2 * g] = __byte_perm(z[0], z[1], 0x6420);
        l[2 * g + 1] = __byte_perm(z[2], z[3], 0x6420);
        n[g] = x0 | __funnelshift_l(x1, x1, 4);
        if (e | ((x0 | x1) & 0x78787878u)) bad |= 1u << g;
        if (g & 1) sts128(g == 1 ? d0 : d1, l[2 * g - 2], l[2 * g - 1], l[2 * g], l[2 * g + 1]);
    }
    sts128(d2, n[0], n[1], n[2], n[3]);
    if (bad) {
        uint32_t i;
        asm volatile("atom.shared.add.u32 %0, [%1], %2;" : "=r"(i) : "r"(pk.cmp + 8 + (d2 >> 31)), "r"(__popc(bad)) : "memory");
#pragma unroll
        for (int g = 0; g < 4; g++) {
            asm volatile("{\n.reg .pred p, q;\n.reg .u32 a;\nsetp.ne.u32 p, %1, 0;\nsetp.lt.and.u32 q, %0, %5, p;\n"
                         "@p st.shared.v2.u32 [%6], {%7, %8};\n@p st.shared.u32 [%9], %10;\nmad.lo.u32 a, %0, 8, %2;\n"
                         "@q st.shared.v2.u32 [a], {%3, %4};\n@p add.u32 %0, %0, 1;\n}"
                         : "+r"(i)
                         : "r"(bad & (1u << g)), "r"(pk.esc), "r"(pk.key | it << 9 | g << 7), "r"(a[4 * g + 3]),
                           "n"(ECAP), "r"((g < 2 ? d0 : d1) + (g & 1) * 8), "r"(a[4 * g]), "r"(a[4 * g + 1]), "r"(d2 + g * 4),
                           "r"(a[4 * g + 2]) : "memory");
        }
    }
    __syncwarp();
}
__device__ __forceinline__ uint32_t esc_flags(const Pack& pk) {
    const uint32_t e = lds32(pk.esc + min(pk.key & 31u, ECAP - 1u) * 8);
    return __reduce_or_sync(0xffffffffu, ((e ^ pk.key) & ~0x79fu) == 0 ? 1u << ((e >> 9) & 3) : 0u);
}
__device__ __forceinline__ void unpack16(uint32_t* a, uint32_t up, uint32_t c, int it, uint32_t flags, const Pack& pk) {
    const uint4 nn = lds128(c + 4096);
    const uint4 l0 = lds128(c), l1 = lds128(c + 2048);
    const uint32_t n[4] = {nn.x, nn.y, nn.z, nn.w};
    const uint32_t l[8] = {l0.x, l0.y, l0.z, l0.w, l1.x, l1.y, l1.z, l1.w};
#pragma unroll
    for (int g = 0; g < 4; g++) {
        const uint32_t h0 = n[g] & 0x87878787u, h1 = __funnelshift_r(n[g], n[g], 4) & 0x87878787u;
        a[4 * g]     = mul2(__byte_perm(l[2 * g], h0, 0x5140), up);
        a[4 * g + 1] = mul2(__byte_perm(l[2 * g], h0, 0x7362), up);
        a[4 * g + 2] = mul2(__byte_perm(l[2 * g + 1], h1, 0x5140), up);
        a[4 * g + 3] = mul2(__byte_perm(l[2 * g + 1], h1, 0x7362), up);
    }
    if (flags >> it & 1) {
        const uint32_t me = pk.key | it << 9;
        const uint2 e = lds64(pk.esc + min(me & 31u, ECAP - 1u) * 8);
        uint32_t hit = __ballot_sync(0xffffffffu, ((e.x ^ me) & ~0x19fu) == 0) & (uint32_t)((1ull << ECAP) - 1);
#pragma unroll 1
        while (hit) {
            const int src = __ffs(hit) - 1;
            hit &= hit - 1;
            const uint32_t d = __shfl_sync(0xffffffffu, e.x, src) ^ me, v = __shfl_sync(0xffffffffu, e.y, src);
            const uint32_t ge = (d >> 7) & 3;
            const uint2 r01 = lds64(c + (ge >> 1) * 2048 + (ge & 1) * 8);
            const uint32_t r2 = lds32(c + 4096 + ge * 4);
#pragma unroll
            for (int g = 0; g < 4; g++)
                if (d == (uint32_t)(g << 7)) { a[4 * g] = r01.x; a[4 * g + 1] = r01.y; a[4 * g + 2] = r2; a[4 * g + 3] = v; }
        }
    }
}

__device__ __forceinline__ void qk_half(float* s, float* s2, const uint32_t* a, uint32_t q) {
    const uint4 q0 = lds128(q), q1 = lds128(q + 256);
    mma(s, a, q0.x, q0.y);
    mma(s2, a + 4, q0.z, q0.w);
    mma(s, a + 8, q1.x, q1.y);
    mma(s2, a + 12, q1.z, q1.w);
}
__device__ __forceinline__ void mma_ones(float* c, uint32_t b) {
    asm volatile("mma.sync.aligned.m16n8k8.row.col.f32.bf16.bf16.f32 {%0,%1,%2,%3}, {%4,%4}, {%5}, {%0,%1,%2,%3};"
                 : "+f"(c[0]), "+f"(c[1]), "+f"(c[2]), "+f"(c[3]) : "r"(0x3f803f80u), "r"(b));
}
template <bool SMALL>
__device__ __forceinline__ void pv_half(Acc& a, const uint32_t* f, uint32_t pa) {
    const uint32_t ones[4] = {0x3f803f80u, 0x3f803f80u, 0x3f803f80u, 0x3f803f80u};
    const uint4 pp = lds128(pa);
    mma(a.o[0], f, pp.x, pp.y);
    mma(a.o[1], f + 4, pp.x, pp.y);
    if (SMALL) { mma_ones(a.l, pp.x); mma_ones(a.l, pp.y); } else mma(a.l, ones, pp.x, pp.y);
    mma(a.o[0], f + 8, pp.z, pp.w);
    mma(a.o[1], f + 12, pp.z, pp.w);
    if (SMALL) { mma_ones(a.l, pp.z); mma_ones(a.l, pp.w); } else mma(a.l, ones, pp.z, pp.w);
}
__device__ __forceinline__ void load_khalf(uint32_t* a, uint32_t k) {
#pragma unroll
    for (int j = 0; j < 4; j++) ldsm4(a + j * 4, k ^ (j << 5));
    __syncwarp();
}
__device__ __forceinline__ void load_vhalf(uint32_t* f, uint32_t v) {
    ldsm4t(f, v);
    ldsm4t(f + 4, v ^ 32);
    ldsm4t(f + 8, v + 2048);
    ldsm4t(f + 12, (v ^ 32) + 2048);
    __syncwarp();
}
__device__ __forceinline__ void park(uint32_t* r, uint32_t kb, uint32_t vb) {
#pragma unroll
    for (int j = 0; j < 12; j++) {
        const int it = j / 3, c = j % 3;
        const uint32_t ad = it < 2 ? (kb ^ (c << 5)) + it * 8192 : (vb ^ ((c & 1) << 5)) + (c >> 1) * 2048 + (it - 2) * 4096;
        const uint4 u = lds128(ad);
        r[4 * j] = u.x; r[4 * j + 1] = u.y; r[4 * j + 2] = u.z; r[4 * j + 3] = u.w;
    }
}
__device__ __forceinline__ void unpark(const uint32_t* r, uint32_t c) {
#pragma unroll
    for (int j = 0; j < 12; j++) sts128(c + j * 2048, r[4 * j], r[4 * j + 1], r[4 * j + 2], r[4 * j + 3]);
}
__device__ __forceinline__ uint32_t k_offset(uint32_t slots, int wj, int lane) {
    const int row = wj * 16 + (lane & 7) + ((lane >> 3) & 1) * 8;
    return slots + row * 128 + (((lane >> 4) ^ (row & 7)) << 4);
}
__device__ __forceinline__ uint32_t v_offset(uint32_t slots, int wj, int lane) {
    const int key = (lane & 7) + (lane >> 4) * 8, cg = wj * 4 + ((lane >> 3) & 1);
    return slots + (cg >> 3) * 8192 + key * 128 + (((cg & 7) ^ (key & 7)) << 4);
}
__device__ __forceinline__ void load_kfrag(uint32_t* rk, uint32_t kb) {
#pragma unroll
    for (int ks = 0; ks < 8; ks++) ldsm4(rk + ks * 4, (kb ^ ((ks & 3) << 5)) + (ks >> 2) * 8192);
}

template <int NPRE>
__device__ __forceinline__ void ln_gemv_part(uint32_t (*f)[8], uint32_t a0, uint32_t a1, uint32_t kstride, uint32_t xw,
                                             int wq, int lane) {
    const int t = lane & 3, g = lane >> 2;
    float c0[4] = {0.f, 0.f, 0.f, 0.f}, c1[4] = {0.f, 0.f, 0.f, 0.f};
#pragma unroll
    for (int ks = 0; ks < 4; ks++) {
        uint32_t* ff = f[ks % NPRE];
        if (ks >= NPRE) {
            ldsm4t(ff, a0 + ks * kstride);
            ldsm4t(ff + 4, a1 + ks * kstride);
        }
        uint32_t xa = __shfl_sync(0xffffffffu, xw, ks * 8 + t), xb = __shfl_sync(0xffffffffu, xw, ks * 8 + 4 + t);
        if (g & 1) xa = xb = 0x3f803f80u;
        mma(c0, ff, xa, xb);
        mma(c1, ff + 4, xa, xb);
    }
    {
        const float a = bf_lo(xw), b = bf_hi(xw);
        const float su = a + b, sq = fmaf(a, a, b * b);
        float keep = (lane & 16) ? sq : su, send = (lane & 16) ? su : sq;
        keep += __shfl_xor_sync(0xffffffffu, send, 16);
#pragma unroll
        for (int k = 8; k > 0; k >>= 1) keep += __shfl_xor_sync(0xffffffffu, keep, k);
        if ((lane & 15) == 0) sts32(SM_RED + (lane >> 4) * 32 + wq * 4, __float_as_uint(keep));
    }
    float y = (t & 2) ? ((t & 1) ? c1[2] : c1[0]) : ((t & 1) ? c0[2] : c0[0]);
    float z = (t & 2) ? ((t & 1) ? c1[3] : c1[1]) : ((t & 1) ? c0[3] : c0[1]);
    sts64(SM_Q + wq * 256 + (t * 8 + g) * 8, __float_as_uint(y), __float_as_uint(z));
}
__device__ __forceinline__ float sum4(uint4 u) {
    return (__uint_as_float(u.x) + __uint_as_float(u.y)) + (__uint_as_float(u.z) + __uint_as_float(u.w));
}
__device__ __forceinline__ float ln_gemv_fin(int lane) {
    float mean, rstd;
    {
        const uint4 a = lds128(SM_RED), b = lds128(SM_RED + 16), c = lds128(SM_RED + 32), d = lds128(SM_RED + 48);
        mean = (sum4(a) + sum4(b)) * (1.f / 512.f);
        const float var = fmaxf(fmaf(sum4(c) + sum4(d), 1.f / 512.f, -mean * mean), 0.f) + 1e-5f;
        asm("rsqrt.approx.ftz.f32 %0, %1;" : "=f"(rstd) : "f"(var));
    }
    uint2 u[8];
#pragma unroll
    for (int j = 0; j < 8; j++) u[j] = lds64(SM_Q + j * 256 + lane * 8);
#define S8(f) (((__uint_as_float(u[0].f) + __uint_as_float(u[1].f)) + (__uint_as_float(u[2].f) + __uint_as_float(u[3].f))) + \
               ((__uint_as_float(u[4].f) + __uint_as_float(u[5].f)) + (__uint_as_float(u[6].f) + __uint_as_float(u[7].f))))
    return (S8(x) - mean * S8(y)) * rstd;
#undef S8
}
__device__ __forceinline__ void ar_add(uint4* dst, float y0, float y1) {
    asm volatile("red.relaxed.gpu.global.add.v4.f32 [%0], {%1, %2, %3, %1};" ::"l"(dst), "f"(1.f), "f"(y0), "f"(y1) : "memory");
}

__device__ __forceinline__ int unit_head(int cta, int wg) { return cta < 128 ? ((cta + (cta >> 3)) & 7) : (cta - 128) * 2 + wg; }
__device__ __forceinline__ int unit_index(int cta, int wg) { return cta < 128 ? (cta >> 3) * 2 + wg : 32; }
__device__ __forceinline__ void issue_item(int j, const Maps& tm, int tb, int ui, uint32_t slots, uint32_t bars) {
    const int slot = (int)((0x1010210432105432ull >> (4 * j)) & 15);
    tma_tile((j & 1) ? &tm.v : &tm.k, tb + (j >> 1) * NUNIT + ui, slots + slot * SLOT, bars + slot * 8);
}
__device__ __forceinline__ void load_ffn(const Maps& tm, int cta, int h, uint32_t z) {
    if (h) {
        tma_rows(&tm.wd, cta * 16, z, SM_WBAR);
    } else {
        expect_tx(SM_WBAR, SLOT);
        tma_2d(&tm.wu, cta * 16, 0, z, SM_WBAR);
        tma_2d(&tm.wu, cta * 16, 256, z + 8192, SM_WBAR);
    }
}
__device__ __forceinline__ void load_wq(const Maps& tm, int cta, int h, uint32_t z) {
    expect_tx(SM_WBAR, SLOT);
    tma_2d(&tm.wq, cta * 32, h * 256, z, SM_WBAR);
}
__device__ __forceinline__ void draw_ticket(uint32_t& ticket, const Params& p, int ph, int head, int lane) {
    asm volatile("{\n.reg .pred p;\nsetp.eq.u32 p, %2, 0;\n@p atom.relaxed.gpu.global.inc.u32 %0, [%1], 0xfffffffe;\n}"
                 : "+r"(ticket) : "l"(&g_s.ticket[ph][head][0]), "r"(lane) : "memory");
}
#define DESC(sk, sv) ((uint32_t)((sk) | ((sv) << 3) | 64))

__device__ __forceinline__ uint4* part_dst(const Params& p, int head, int ui, int tid) {
    const int lane = tid & 31, g = lane >> 2, t = lane & 3;
    return &g_s.part[(head * 4 + 2 * (t & 1) + (t >> 1)) * 4 + ((tid >> 5) & 3)][g >> 1][ui][g & 1];
}
__device__ __forceinline__ uint4* q_dst(const Params& p, int layer, int cta, int lane) {
    return &g_s.q[layer][(lane >> 3) & 1][cta >> 4][((cta & 3) * 16 + ((cta >> 2) & 3) * 4) * 2 + (lane & 7)];
}
__device__ __forceinline__ void publish_q(uint4* out, float r, uint32_t tag, int lane) {
    const int src = (lane & 1) * 16 + ((lane >> 1) & 3) * 2;
    const float q0 = __shfl_sync(0xffffffffu, r, src), q1 = __shfl_sync(0xffffffffu, r, src + 1);
    const float q2 = __shfl_sync(0xffffffffu, r, src + 8), q3 = __shfl_sync(0xffffffffu, r, src + 9);
    if (lane < 16) ll_st(out, pack_bf16(q0, q1), tag, pack_bf16(q2, q3), tag);
}

template <bool TAIL>
__device__ __forceinline__ void gemv_chain(const Maps& tm, const Params& p, const int cta, const uint32_t tag) {
    constexpr uint32_t Z_WO = SM_SLOTS + (TAIL ? 2 : 0) * SLOT, Z_GU = SM_SLOTS + (TAIL ? 3 : 0) * SLOT;
    [[maybe_unused]] constexpr int TB = TAIL ? 16 : 0;
    const int wq = __shfl_sync(0xffffffffu, tid_now() >> 5, 0);
    uint32_t xo;
    {
        const int lane = tid_now() & 31, g = lane >> 2, t = lane & 3;
        if (!TAIL) {
            const unsigned short* xp = reinterpret_cast<const unsigned short*>(p.x) + wq * 64 + t * 16 + g;
            xo = xp[0] | (uint32_t)xp[8] << 16;
            if (wq == 0 && lane < 16) ll_st(q_dst(p, 1, cta, lane), 0, 0, 0, 0);
            __syncwarp();
            if (wq == 1) l2_prefetch(&g_s.ar[0][0][0][0] + (cta & 63) * 128, 2048, POL_NORMAL);
        } else {
            unsigned long long u;
            uint32_t it = 0;
            do {
                spin_guard(it);
                asm volatile("ld.relaxed.gpu.global.b64 %0, [%1];" : "=l"(u) : "l"(&g_s.x2[wq * 32 + lane]) : "memory");
            } while (__any_sync(0xffffffffu, (uint32_t)(u >> 32) != tag - 1));
            xo = (uint32_t)u;
        }
        const uint32_t t16 = tag & 0xffffu;
        const uint4* src = &g_s.part[cta][wq][lane & 15][lane >> 4];
        const bool three = (lane & 15) == 0;
        if (wq == 0) {
            const uint32_t target = ((tag >> 2) * 2 + (TAIL ? 2 : 1)) * (2 * NCTA);
            uint32_t it = 0;
            bool pf = !TAIL;
            while (true) {
                uint32_t v;
                asm volatile("ld.acquire.gpu.global.u32 %0, [%1];" : "=r"(v) : "l"(&g_s.done[0]) : "memory");
                const int rem = __shfl_sync(0xffffffffu, (int)(target - v), 0);
                if (pf && rem <= PF_REM) {
                    pf = false;
                    l2_prefetch(p.wu + (size_t)cta * 14336, 14336, POL_FIRST);
                    l2_prefetch(p.wd + (size_t)cta * 14336, 14336, POL_FIRST);
                }
                if (rem <= 0) break;
                spin_guard(it);
                if (rem > 16) delay_cycles(400);
            }
        }
        __syncthreads();
        TS(TB + 14);
        uint4 a = ll_ld_last(src), b = ll_ld_last(src + 32), e = make_uint4(0, 0xff800000u | t16, 0, t16);
        if (three) e = ll_ld_last(src + 64);
        const uint32_t wa0 = Z_WO + wq * 2048 + ((lane & 7) + (lane >> 4) * 8) * 128 + ((((lane >> 3) & 1) ^ (lane & 7)) << 4);
        uint32_t f0[4][4], f1[4][4];
        mbar_wait(TAIL ? SM_TBAR : SM_WBAR, TAIL ? 0 : 1);
        __syncwarp();
        if (TAIL) {
#pragma unroll
            for (int mt = 0; mt < 4; mt++) {
                ldsm4t(f0[mt], wa0 ^ (mt << 5));
                ldsm4t(f1[mt], (wa0 ^ (mt << 5)) + USTR);
            }
        }
        {
            uint32_t it = 0;
            while (__any_sync(0xffffffffu, ((a.y ^ t16) | (a.w ^ t16) | (b.y ^ t16) | (b.w ^ t16) | (e.y ^ t16) | (e.w ^ t16)) << 16 != 0)) {
                spin_guard(it);
                a = ll_ld_last(src);
                b = ll_ld_last(src + 32);
                if (three) e = ll_ld_last(src + 64);
            }
        }
        TS(TB + 0);
        if (!TAIL && wq >= 6) l2_prefetch(p.wq + (size_t)(cta + (wq - 6) * 128) * 16384, 16384, POL_FIRST);
        const float la = __uint_as_float(__byte_perm(a.w, a.y, 0x7632)), lb = __uint_as_float(__byte_perm(b.w, b.y, 0x7632));
        const float le = __uint_as_float(__byte_perm(e.w, e.y, 0x7632));
        float mm;
        {
            int k = __float_as_int(fmaxf(fmaxf(la, lb), le));
            k ^= (k >> 31) & 0x7fffffff;
            k = __reduce_max_sync(0xffffffffu, k);
            k ^= (k >> 31) & 0x7fffffff;
            mm = __int_as_float(k);
        }
        const float wa = ex2(la - mm), wb = ex2(lb - mm), we = ex2(le - mm);
        const float v0 = fmaf(we, __uint_as_float(e.x), fmaf(wb, __uint_as_float(b.x), wa * __uint_as_float(a.x)));
        const float v1 = fmaf(we, __uint_as_float(e.z), fmaf(wb, __uint_as_float(b.z), wa * __uint_as_float(a.z)));
        float ws = wa + wb + we;
        float kk = (lane & 8) ? v1 : v0;
        kk += __shfl_xor_sync(0xffffffffu, (lane & 8) ? v0 : v1, 8);
        ws += __shfl_xor_sync(0xffffffffu, ws, 8);
        if (!TAIL) {
#pragma unroll
            for (int mt = 0; mt < S1_NPRE; mt++) {
                ldsm4t(f0[mt], wa0 ^ (mt << 5));
                ldsm4t(f1[mt], (wa0 ^ (mt << 5)) + USTR);
            }
        }
#pragma unroll
        for (int k = 4; k > 0; k >>= 1) {
            kk += __shfl_xor_sync(0xffffffffu, kk, k);
            ws += __shfl_xor_sync(0xffffffffu, ws, k);
        }
        {
            float r; asm("rcp.approx.ftz.f32 %0, %1;" : "=f"(r) : "f"(ws));
            const uint32_t o = pack_bf16(kk * r, 0.f);
            if ((lane & 7) == 0) sts16(SM_RED + 128 + (wq & 3) * 16 + (wq >> 2) * 8 + ((lane >> 3) & 1) * 4 + (lane >> 4) * 2, o);
        }
        uint4* out = &g_s.ar[TAIL ? 2 : 0][cta & 1][wq * 16 + (lane >> 1)][lane & 1];
        __syncthreads();
        TS(TB + 1);
        const uint4 ob = lds128(SM_RED + 128 + t * 16);
        float c0[4] = {0.f, 0.f, 0.f, 0.f}, c1[4] = {0.f, 0.f, 0.f, 0.f};
#pragma unroll
        for (int mt = 0; mt < 4; mt++) {
            constexpr int NP = TAIL ? 4 : S1_NPRE;
            uint32_t* g0 = f0[mt % NP];
            uint32_t* g1 = f1[mt % NP];
            if (mt >= NP) {
                ldsm4t(g0, wa0 ^ (mt << 5));
                ldsm4t(g1, (wa0 ^ (mt << 5)) + USTR);
            }
            const bool mine = (g >> 1) == mt;
            mma(c0, g0, mine ? ob.x : 0u, mine ? ob.y : 0u);
            mma(c1, g1, mine ? ob.z : 0u, mine ? ob.w : 0u);
        }
        ar_add(out, c0[0] + c1[0], c0[2] + c1[2]);
        TS(TB + 2);
        if (!TAIL) {
            if (wq == 4 || wq == 5) bar_sync(4, 256); else bar_arrive(4, 256);
        }
    }
#pragma unroll 1
    for (int hv = 0; hv < 2; hv++) {
        const int half = __shfl_sync(0xffffffffu, hv, 0);
        const bool ffn = cta < 112;
        if (TAIL && (half ? cta != 0 : !ffn)) break;
        uint32_t t0;
        asm volatile("mov.u32 %0, %%clock;" : "=r"(t0));
        const int lane = tid_now() & 31, g = lane >> 2, t = lane & 3;
        const bool qs = !TAIL && half;
        [[maybe_unused]] const int h = wq - 4;
        [[maybe_unused]] const uint32_t z = SM_SLOTS + h * USTR;
        if (!TAIL && (wq == 4 || wq == 5)) {
            if (!half) {
                if (ffn) load_ffn(tm, cta, h, z);
            } else if (!(WQ_EARLY && ffn && h == 0)) {
                if (!ffn) delay_cycles(D_SKIP);
                load_wq(tm, cta, h, z);
            }
        }
        constexpr int NPRE = TAIL ? 4 : MID_NPRE;
        uint32_t f[NPRE][8];
        const int row = (wq & 3) * 64 + (lane & 7) + (lane >> 4) * 8;
        const uint32_t a0 = qs ? SM_SLOTS + (wq >> 2) * USTR + row * 64 + ((((lane >> 3) & 1) ^ ((lane >> 1) & 3)) << 4)
                               : SM_WG + (wq >> 2) * 8192 + row * 32 + ((((lane >> 3) ^ (lane >> 2)) & 1) << 4);
        const uint32_t a1 = qs ? a0 ^ 32 : a0 - (SM_WG - Z_GU), kstride = qs ? 1024 : 512;
        {
            const uint4* src = &g_s.ar[(TAIL ? 2 : 0) + half][0][wq * 16 + (lane >> 1)][lane & 1];
            const uint32_t cnt = __float_as_uint(half ? 56.f : 64.f);
            if (TAIL && !half) {
                mbar_wait(SM_WBAR, 0);
                __syncwarp();
#pragma unroll
                for (int ks = 0; ks < NPRE; ks++) {
                    ldsm4t(f[ks], a0 + ks * kstride);
                    ldsm4t(f[ks] + 4, a1 + ks * kstride);
                }
            }
            {
                const uint32_t d = (half && !ffn) ? D_AR + D_SKIP : D_AR;
                uint32_t t1;
                do { asm volatile("mov.u32 %0, %%clock;" : "=r"(t1)); } while (t1 - t0 < d);
            }
            uint4 u, v;
            uint32_t it = 0;
            do {
                spin_guard(it);
                u = ll_ld(src);
                v = ll_ld(src + 1024);
            } while (__any_sync(0xffffffffu, u.x != cnt || u.w != cnt || v.x != cnt || v.w != cnt));
            const uint32_t y = pack_bf16(__uint_as_float(u.y) + __uint_as_float(v.y), __uint_as_float(u.z) + __uint_as_float(v.z));
            xo = pack_bf16(bf_lo(xo) + bf_lo(y), bf_hi(xo) + bf_hi(y));
        }
        if (half) TS(TB + 7); else TS(TB + 3);
        if (!half && !ffn) continue;
        const uint32_t xw = movm(xo);
        if (TAIL && half) {
            reinterpret_cast<uint32_t*>(p.out)[wq * 32 + lane] = xw;
            if (wq == 0) {
                if (lane < 16) g_s.ticket[lane >> 3][lane & 7][0] = 0;
                if (lane == 16) g_s.epoch = (tag >> 2) + 1;
            }
            break;
        }
        if (!TAIL) {
            mbar_wait(SM_WBAR, qs && ffn);
            __syncwarp();
#pragma unroll
            for (int ks = 0; ks < NPRE; ks++) {
                ldsm4t(f[ks], a0 + ks * kstride);
                ldsm4t(f[ks] + 4, a1 + ks * kstride);
            }
        }
        if (half) TS(8); else TS(TB + 4);
        ln_gemv_part<NPRE>(f, a0, a1, kstride, xw, wq, lane);
        const uint32_t wd0 = Z_GU + USTR + wq * 2048 + ((lane & 7) + (lane >> 4) * 8) * 128 + ((((lane >> 3) & 1) ^ (lane & 7)) << 4);
        uint32_t d[4][4];
        constexpr int DPRE = TAIL ? 4 : MID_DPRE;
#pragma unroll
        for (int mt = 0; mt < DPRE; mt++) ldsm4t(d[mt], wd0 ^ (mt << 5));
        uint4* out = qs ? q_dst(p, 1, cta, lane) : &g_s.ar[TAIL ? 3 : 1][cta & 1][wq * 16 + (lane >> 1)][lane & 1];
        __syncthreads();
        if (!half) TS(TB + 5);
        if (WQ_EARLY && !TAIL && !half && wq == 4) load_wq(tm, cta, 0, z);
        float r = ln_gemv_fin(lane);
        if (qs) {
            if (wq == 0) publish_q(out, r, tag, lane);
            if (cta == 0)
                asm volatile("st.relaxed.gpu.global.b64 [%0], %1;" ::"l"(&g_s.x2[wq * 32 + lane]), "l"((unsigned long long)tag << 32 | xo) : "memory");
            __syncthreads();
            TS(9);
            break;
        }
        r = bf16r(r);
        const float up = __shfl_down_sync(0xffffffffu, r, 16);
#pragma unroll
        for (int mt = DPRE; mt < 4; mt++) ldsm4t(d[mt], wd0 ^ (mt << 5));
        const float hh = (r > 0.f ? r : 0.f * r) * up;
        const float h0 = __shfl_sync(0xffffffffu, hh, 2 * t), h1 = __shfl_sync(0xffffffffu, hh, 2 * t + 1);
        const float h2 = __shfl_sync(0xffffffffu, hh, 2 * t + 8), h3 = __shfl_sync(0xffffffffu, hh, 2 * t + 9);
        const uint32_t b0 = pack_bf16(h0, h1), b1 = pack_bf16(h2, h3);
        float c0[4] = {0.f, 0.f, 0.f, 0.f}, c1[4] = {0.f, 0.f, 0.f, 0.f};
#pragma unroll
        for (int mt = 0; mt < 4; mt++) {
            const bool mine = (g >> 1) == mt;
            mma((mt & 1) ? c1 : c0, d[mt], mine ? b0 : 0u, mine ? b1 : 0u);
        }
        ar_add(out, c0[0] + c1[0], c0[2] + c1[2]);
        TS(TB + 6);
        if (!TAIL) {
            if (wq == 4 || wq == 5) bar_sync(4, 256); else bar_arrive(4, 256);
        }
    }
}

#define UVARS                                                                                               \
    const int wqu = __shfl_sync(0xffffffffu, tid_now() >> 5, 0);                                            \
    const int wg = wqu >> 2, wj = wqu & 3;                                                                  \
    [[maybe_unused]] const int head = unit_head(cta, wg), ui = unit_index(cta, wg), tb = head * NTILE;      \
    [[maybe_unused]] const uint32_t slots = SM_SLOTS + wg * USTR, bars = SM_BAR + wg * 48;                  \
    [[maybe_unused]] const int barid = 1 + wg;                                                              \
    [[maybe_unused]] const uint32_t qbase = cta < 128 ? SM_Q : SM_WG + wg * 1024;                           \
    [[maybe_unused]] const uint32_t rec = SM_ST + wg * 16;                                                  \
    [[maybe_unused]] const uint32_t mx = SM_MX + wg * 64;
#define Q_RD (qbase + (lane & 15) * 16)
#define P_RD (SM_P + wg * 512 + (lane & 15) * 16)
#define P_WR (SM_P + wg * 512 + (wj >> 1) * 256 + (wj & 1) * 8 + (lane & 15) * 16)

__device__ __forceinline__ void static_phase(const Maps& tm, const int cta, Acc& acc, uint32_t (*rp)[48]) {
    UVARS
#pragma unroll 1
    for (int rv = 0; rv < NSTAT; rv++) {
        const int rn = __shfl_sync(0xffffffffu, rv, 0);
        const int lane = tid_now() & 31;
        const uint32_t d = (uint32_t)(0x10210432105432ull >> (8 * rn)), par = 0x7c0u >> (2 * rn);
        const int sk = d & 7, sv = (d >> 4) & 7;
        Pack pk;
        pk.cmp = SM_CMP + wg * 16;
        pk.esc = SM_ESC + wg * (ECAP * 8);
        pk.key = (rn < 4 ? rn + 3 : 6 - rn) << 11 | wj << 5 | lane;
        const bool inplace = rn < 4;
        uint32_t dst = slots + 2 * SLOT + (6 - rn) * 24576 + (wj * 32 + lane) * 16;
        uint32_t kb = k_offset(slots, wj, lane) + sk * SLOT;
        float s[4] = {0.f, 0.f, 0.f, 0.f}, s2[4] = {0.f, 0.f, 0.f, 0.f};
        uint32_t a[16];
        mbar_wait(bars + sk * 8, par & 1);
        __syncwarp();
        {
            const uint32_t b4 = lds32(pk.cmp);
#pragma unroll SUNR
            for (int hv = 0; hv < 2; hv++) {
                const int h = __shfl_sync(0xffffffffu, hv, 0);
                load_khalf(a, kb);
                pack16(a, b4, inplace ? kb : dst, inplace ? kb ^ 32 : dst + 2048, inplace ? kb ^ 64 : dst + 4096, h, pk);
                qk_half(s, s2, a, Q_RD + h * 512);
                kb += 8192; dst += 6144;
            }
        }
#pragma unroll
        for (int i = 0; i < 4; i++) s[i] += s2[i];
        softmax_step(s, acc, P_WR, mx, barid, lane, wj);
        uint32_t vb = v_offset(slots, wj, lane) + sv * SLOT;
        mbar_wait(bars + sv * 8, (par >> 1) & 1);
        __syncwarp();
        {
            const uint32_t b4 = lds32(pk.cmp + 4);
#pragma unroll SUNR
            for (int yv = 0; yv < 2; yv++) {
                const int y = __shfl_sync(0xffffffffu, yv, 0);
                load_vhalf(a, vb);
                pack16(a, b4, inplace ? vb : dst, inplace ? vb ^ 32 : dst + 2048, inplace ? vb + 2048 : dst + 4096, 2 + y, pk);
                pv_half<true>(acc, a, SM_P + wg * 512 + (tid_now() & 15) * 16 + y * 256);
                vb += 4096; dst += 6144;
            }
            vb -= 8192;
        }
        {
            const uint32_t kb2 = k_offset(slots, wj, tid_now() & 31) + sk * SLOT;
            if (rn == 0) park(rp[0], kb2, vb);
            if (rn == 1) park(rp[1], kb2, vb);
            if (rn == 2) park(rp[2], kb2, vb);
            if (rn == 3) park(rp[3], kb2, vb);
        }
        asm volatile("fence.proxy.async.shared::cta;" ::: "memory");
        wg_bar_or(barid, false);
        const int j = (int)((wj == 1 ? 0xe0c0a86u : 0xfd0b907u) >> (4 * rn)) & 15;
        if ((wj == 1 || wj == 2) && j) issue_item(j, tm, tb, ui, slots, bars);
        if (wj == 0) {
            const uint32_t st = lds32(rec + 4);
            if (lane == 0 && lds32(pk.cmp + 8) > ECAP) {
                sts16(SM_KEEP + wg * 64 + (st & 255) * 2, rn * NUNIT + ui);
                sts32(rec + 4, (st + 1) | 0x10000u << (pk.key >> 11));
            }
            __syncwarp();
        }
    }
    TSD(28);
    if (wqu == 0) __threadfence();
    wg_bar_or(barid, false);
}

__device__ __forceinline__ void acc_init(Acc& a) {
#pragma unroll
    for (int i = 0; i < 4; i++) { a.o[0][i] = 0.f; a.o[1][i] = 0.f; a.l[i] = 0.f; }
    a.m0 = a.m1 = __int_as_float(0xff800000);
}

__device__ __forceinline__ void attention_pass(const Maps& tm, const Params& p, const int cta, const int ph, const uint32_t tag0,
                                               Acc& acc, uint32_t (*rp)[48], float* s) {
    UVARS
    const int lim = ph ? T_KEEP0 : NTILE;
    uint32_t ticket = 0;
    if (wj == 0) draw_ticket(ticket, p, ph, head, tid_now() & 31);
    const uint32_t st0 = __shfl_sync(0xffffffffu, lds32(rec + 4), 0);
    uint32_t phbits = __shfl_sync(0xffffffffu, lds32(rec + 12), 0);
    int nk = st0 & 255;
    uint32_t cur = DESC(0, 1) | 256;
    uint32_t q0 = 0, q1 = 0;
    int rn = NSTAT, ki = 0, since = KRATIO;
    bool open = true;
    if (ph) {
        rn = 0; q0 = cur; cur = 128 | 8;
        if (nk > 0 && __shfl_sync(0xffffffffu, (int)lds16(SM_KEEP + wg * 64 + nk * 2 - 2), 0) >= T_KEEP0) nk--;
        else cur |= 512;
    }
#pragma unroll 1
    while (true) {
        const int lane = tid_now() & 31;
        const uint32_t rel = cur ? cur : (rn == 1 ? DESC(2, 3) : 0);
        const int sk = rel & 7, sv = (rel >> 3) & 7;
        const bool keeps = ph && ki < nk && (rel & 64);
        const bool want = (rel & 64) && open && (!(q0 & 256) || (keeps && since < KRATIO));
        int tkeep = 0;
        if (keeps) tkeep = __shfl_sync(0xffffffffu, lds16(SM_KEEP + wg * 64 + ki * 2), 0);
        const bool resid = rn + (cur == 0) < NSTAT;
#define PUBLISH()                                                                                                          \
        if (wj == 0) {                                                                                                     \
            uint32_t lb = 0;                                                                                               \
            if (resid && q0 && mbar_test(bars + ((q0 >> 3) & 7) * 8, (phbits >> ((q0 >> 3) & 7)) & 1)) lb = 0x10000u;      \
            asm volatile("{\n.reg .pred p, q;\n.reg .u32 w;\nmov.u32 w, %6;\nsetp.eq.u32 p, %7, 0;\n@p bra.uni N_%=;\n"  \
                         "shfl.sync.idx.b32 w, %1, 0, 31, 0xffffffff;\nadd.u32 w, w, %5;\nmin.u32 w, w, %6;\nN_%=:\n"      \
                         "setp.eq.u32 p, %2, 0;\nsetp.ge.and.u32 q, w, %3, p;\nor.b32 w, w, %8;\n@q or.b32 w, w, 0x20000;\n" \
                         "@p st.shared.u32 [%0], w;\n@q red.relaxed.gpu.global.add.u32 [%4], 1;\n}"                        \
                         ::"r"(rec), "r"(ticket), "r"(lane), "r"((!resid && !q0 && !keeps) ? lim : NTILE + 1),             \
                           "l"(&g_s.done[lane]), "n"(T_DYN0 + NUNIT), "n"(NTILE), "r"((uint32_t)want), "r"(lb) : "memory"); \
        }
        if (cur ? !(cur & 512) : !(st0 >> (16 + rn) & 1)) {
            Pack pk;
            pk.cmp = SM_CMP + wg * 16;
            pk.esc = SM_ESC + wg * (ECAP * 8);
            pk.key = rn << 11 | wj << 5 | lane;
            uint32_t a[16], vb, flags = 0;
            if (cur) {
                vb = v_offset(slots, wj, lane) + sv * SLOT;
                if (cur & 64) {
                    const uint32_t kb = k_offset(slots, wj, lane) + sk * SLOT;
                    float s2[4] = {0.f, 0.f, 0.f, 0.f};
                    s[0] = s[1] = s[2] = s[3] = 0.f;
                    mbar_wait(bars + sk * 8, (phbits >> sk) & 1);
                    __syncwarp();
                    if (DBG_U && ph == DBG_PH) TSW(26);
                    load_khalf(a, kb);
                    qk_half(s, s2, a, Q_RD);
                    load_khalf(a, kb + 8192);
                    qk_half(s, s2, a, Q_RD + 512);
                    mbar_wait(bars + sv * 8, (phbits >> sv) & 1);
                    __syncwarp();
                    phbits ^= 1u << sk | 1u << sv;
#pragma unroll
                    for (int i = 0; i < 4; i++) s[i] += s2[i];
                }
                load_vhalf(a, vb);
            } else {
                vb = slots + 2 * SLOT + min(rn, 2) * 24576 + (wj * 32 + lane) * 16;
                flags = esc_flags(pk);
                if (rn == 3) unpark(rp[0], vb);
                if (rn == 4) unpark(rp[1], vb);
                if (rn == 5) unpark(rp[2], vb);
                if (rn == 6) unpark(rp[3], vb);
                const uint2 b4 = lds64(pk.cmp);
                float s2[4] = {0.f, 0.f, 0.f, 0.f};
                s[0] = s[1] = s[2] = s[3] = 0.f;
#pragma unroll RUNR
                for (int h = 0; h < 2; h++) {
                    unpack16(a, b4.x, vb + h * 6144, h, flags, pk);
                    qk_half(s, s2, a, Q_RD + h * 512);
                }
                unpack16(a, b4.y, vb + 12288, 2, flags, pk);
#pragma unroll
                for (int i = 0; i < 4; i++) s[i] += s2[i];
            }
            softmax_step(s, acc, P_WR, mx, barid, lane, wj);
            pv_half<false>(acc, a, P_RD);
            if (cur) load_vhalf(a, vb + 4096);
            else unpack16(a, lds32(pk.cmp + 4), vb + 18432, 3, flags, pk);
            pv_half<false>(acc, a, P_RD + 256);
        } else {
            wg_bar_or(barid, false);
        }
        PUBLISH();
        bar_sync(8 + wg, 128);
        const uint32_t w = __shfl_sync(0xffffffffu, lds32(rec), 0);
        if (w & 0x20000u) break;
        if (cur == 0) rn++;
        int tv = w & 0xffff;
        uint32_t push = 0;
        const bool streamed = tv < lim;
        if (streamed) push = (rel & 127) | 256;
        else if (keeps) { tv = tkeep; push = rel & 127; }
        else if (cur & 128) tv = T_DYN0 + ui;
        if (wj == 1 ? push != 0 : wj == 2 && (push | (cur & 128))) {
            const int sl = wj == 1 ? sk : sv;
            tma_tile(wj == 1 ? &tm.k : &tm.v, tb + tv, slots + sl * SLOT, bars + sl * 8);
            if (!ph && tv >= T_KEEP0 && tv < T_KEEPEND) l2_prefetch((wj == 1 ? p.k : p.v) + (size_t)(tb + tv) * SLOT, SLOT, POL_NORMAL);
        }
        if (streamed) {
            since++;

            if (!ph && tv >= T_KEEP0) {
                if (wj == 3 && lane == 0) sts16(SM_KEEP + wg * 64 + nk * 2, tv);
                nk++;
                if (nk >= KEEPCAP) open = false;
            }
            if (open && wj == 0) draw_ticket(ticket, p, ph, head, lane);
        } else {
            if (want) open = false;
            if (keeps) { ki++; since = 0; }
        }
        if (q0) q1 |= push; else q0 = push;
        if (resid && (q0 == 0 || (!(w & 0x10000u) && (rn < 2 || streamed)))) {
            cur = 0;
        } else {
            cur = q0; q0 = q1; q1 = 0;
        }
    }
    const int lane = tid_now() & 31;
    {
        const int e = (lane >> 1) & 1;
        float l = e ? acc.l[1] : acc.l[0], m = e ? acc.m1 : acc.m0;
        float inv; asm("rcp.approx.ftz.f32 %0, %1;" : "=f"(inv) : "f"(l));
        float lg; asm("lg2.approx.ftz.f32 %0, %1;" : "=f"(lg) : "f"(l));
        uint32_t lam = __float_as_uint(m + lg);
        const uint32_t t16 = (tag0 + ph + 1) & 0xffffu;
        uint32_t ta = (lam & 0xffff0000u) | t16, tc = (lam << 16) | t16;
        uint4* dst = part_dst(p, head, ui, wqu * 32 + lane);
        ll_st(dst, __float_as_uint((e ? acc.o[0][1] : acc.o[0][0]) * inv), ta,
                   __float_as_uint((e ? acc.o[0][3] : acc.o[0][2]) * inv), tc);
        ll_st(dst + 4 * NUNIT * 2, __float_as_uint((e ? acc.o[1][1] : acc.o[1][0]) * inv), ta,
                                   __float_as_uint((e ? acc.o[1][3] : acc.o[1][2]) * inv), tc);
    }
    if (ph) TSW(38); else TSW(36);
    if (wj == 0 && lane == 0) {
        sts32(rec + 4, nk | (st0 & 0xffff0000u));
        sts32(rec + 12, phbits);
    }
}

__global__ void __launch_bounds__(256, 1)
fused_kernel(const __grid_constant__ Maps tm, const Params p) {
    extern __shared__ __align__(1024) unsigned char smem_raw[];
    const int cta = blockIdx.x;
    const bool worker = cta < 128;
    uint32_t tag0;
    if ((uint32_t)__cvta_generic_to_shared(smem_raw) != SM_BASE) __trap();
    TS(40);
    uint32_t rp[4][48];
    Acc acc;
    {
        UVARS
        const int lane = tid_now() & 31;
        if (wj == 0) {
#pragma unroll
            for (int i = 0; i < 6; i++) mbar_init(bars + i * 8, 1);
            mbar_init(SM_WBAR + wg * 8, 2);
            mbar_init(SM_DBAR + wg * 8, 1);
            asm volatile("fence.proxy.async.shared::cta;" ::: "memory");
            __syncwarp();
            if (worker && wg == 0) {
                load_wq(tm, cta, 0, SM_SLOTS + SLOT);
                load_wq(tm, cta, 1, SM_SLOTS + USTR + SLOT);
            }
            issue_item(0, tm, tb, ui, slots, bars);
            issue_item(1, tm, tb, ui, slots, bars);
            if (worker && wg == 0 && lane < 16) ll_st(q_dst(p, 0, cta, lane), 0, 0, 0, 0);
        }
        if (wj == 1) {
            if (lane < ECAP) sts64(SM_ESC + wg * (ECAP * 8) + lane * 8, 0xffffffffu, 0);
            if (lane < 2) sts128(rec + lane * 32, 0, 0, 0, 0x27);
        }
        if (wj == 2) {
            const uint4 u = *reinterpret_cast<const uint4*>(p.x + wg * 256 + lane * 8);
            sts128(SM_P + wg * 512 + lane * 16, u.x, u.y, u.z, u.w);
        }
        if (wqu == 7 && worker && lane < 16) ll_st(&g_s.ar[0][0][0][0] + (cta * 8 + (lane >> 1)) * 8 + (lane & 1), 0, 0, 0, 0);
        if (wqu == 3) {
            uint32_t e;
            asm volatile("ld.relaxed.gpu.global.u32 %0, [%1];" : "=r"(e) : "l"(&g_s.epoch) : "memory");
            sts32(SM_RED, e * 4 + 1);
        }
        __syncthreads();
        tag0 = __shfl_sync(0xffffffffu, lds32(SM_RED), 0);
        const uint32_t xw = lds32(SM_P + wqu * 128 + lane * 4);
        __syncthreads();
        uint32_t it = 0;
        int item = 2;
#pragma unroll 1
        for (int stage = worker ? 0 : 1; stage < 3 || item < 6;) {
            if (item < (stage ? 6 : 5) && (wj != 1 || stage == 3 || mbar_test(bars + item * 8, 0))) {
                if (wj == 1) issue_item(item, tm, tb, ui, slots, bars);
                item++;
                continue;
            }
            spin_guard(it);
            if (stage == 0) {
                if (!mbar_test(SM_WBAR, 0)) continue;
                TS(32);
                const int row = wj * 64 + (lane & 7) + (lane >> 4) * 8;
                const uint32_t a0 = slots + SLOT + row * 64 + ((((lane >> 3) & 1) ^ ((lane >> 1) & 3)) << 4);
                uint32_t f[1][8];
                ldsm4t(f[0], a0);
                ldsm4t(f[0] + 4, a0 ^ 32);
                ln_gemv_part<1>(f, a0, a0 ^ 32, 1024, xw, wqu, lane);
                __syncthreads();
                if (wqu == 0) publish_q(q_dst(p, 0, cta, lane), ln_gemv_fin(lane), tag0, lane);
                if (wqu == 6 && cta < 112) {
                    expect_tx(SM_DBAR, SLOT);
                    tma_2d(&tm.wg, cta * 16, 0, SM_WG, SM_DBAR);
                    tma_2d(&tm.wg, cta * 16, 256, SM_WG + 8192, SM_DBAR);
                }
                __syncthreads();
                TS(33);
            } else if (stage == 1) {
                if (!mbar_test(bars + 2 * 8, 0) || !mbar_test(bars + 3 * 8, 0)) continue;
#pragma unroll 1
                for (int h = 0; h < 4; h++) {
                    uint32_t r[16], m = 0;
                    load_khalf(r, k_offset(slots, wj, lane) + 2 * SLOT + h * 8192);
#pragma unroll
                    for (int j = 0; j < 16; j++) m = __vmaxu2(m, r[j] & 0x7fff7fffu);
                    m = __reduce_max_sync(0xffffffffu, max(m >> 23, (m >> 7) & 0xffu));
                    if (lane == 0)
                        asm volatile("red.shared.max.u32 [%0], %1;" ::"r"(SM_CMP + wg * 16 + (h & 2) * 2),
                                     "r"((min(max(m, 15u), 141u) + 112u) * 0x00800080u) : "memory");
                    __syncwarp();
                }
            } else {
                const uint4 v = ll_ld(&g_s.q[0][cta >> 7][head][wj * 32 + lane]);
                if (__any_sync(0xffffffffu, v.y != tag0 || v.w != tag0)) { delay_cycles(200); continue; }
                sts64(qbase + (wj * 32 + lane) * 8, v.x, v.z);
            }
            stage++;
        }
        wg_bar_or(barid, false);
        TS(34);
#pragma unroll
        for (int i = 0; i < 4; i++)
#pragma unroll
            for (int j = 0; j < 48; j++) asm volatile("" : "=r"(rp[i][j]));
        acc_init(acc);
    }
    static_phase(tm, cta, acc, rp);
    float s[4] = {0.f, 0.f, 0.f, 0.f};
#pragma unroll 1
    for (int phv = 0;; phv = 1) {
        const int ph = __shfl_sync(0xffffffffu, phv, 0);
        attention_pass(tm, p, cta, ph, tag0, acc, rp, s);
        if (ph) break;
        uint32_t rx[32];
        {
            UVARS
            load_kfrag(rx, k_offset(slots, wj, tid_now() & 31));
            wg_bar_or(barid, false);
            if (worker && wj == 3) tma_rows(&tm.wo, cta * 32 + wg * 16, slots, SM_WBAR);
            if (cta < 112) mbar_wait(SM_DBAR, 0);
            __syncwarp();
        }
        if (worker) gemv_chain<false>(tm, p, cta, tag0 + 1);
        UVARS
        const int lane = tid_now() & 31;
        const uint4* src = &g_s.q[1][cta >> 7][head][wj * 32 + lane];
        uint4 v;
        uint32_t it = 0;
        do {
            spin_guard(it);
            if (it == 1 || !worker) delay_cycles(D_AG);
            v = ll_ld(src);
            if (it == 1 && wj == 1) tma_tile(&tm.k, tb + T_DYN0 + ui, slots, bars);
        } while (__any_sync(0xffffffffu, v.y != tag0 + 1 || v.w != tag0 + 1));
        sts64(qbase + (wj * 32 + lane) * 8, v.x, v.z);
        wg_bar_or(barid, false);
        TS(10);
        float s2[4] = {0.f, 0.f, 0.f, 0.f};
        s[0] = s[1] = s[2] = s[3] = 0.f;
        qk_half(s, s2, rx, Q_RD);
        qk_half(s, s2, rx + 16, Q_RD + 512);
#pragma unroll
        for (int i = 0; i < 4; i++) s[i] += s2[i];
        acc_init(acc);
    }
    if (worker) {
        UVARS
        if (wj == 3) tma_rows(&tm.wo, cta * 32 + wg * 16, slots + 2 * SLOT, SM_TBAR);
        if (wj == 2 && cta < 112) load_ffn(tm, cta, wg, slots + 3 * SLOT);
        gemv_chain<true>(tm, p, cta, tag0 + 2);
    }
}

typedef CUresult (*EncodeFn)(CUtensorMap*, CUtensorMapDataType, cuuint32_t, void*, const cuuint64_t*, const cuuint64_t*,
                             const cuuint32_t*, const cuuint32_t*, CUtensorMapInterleave, CUtensorMapSwizzle,
                             CUtensorMapL2promotion, CUtensorMapFloatOOBfill);

void make_map(EncodeFn encode, CUtensorMap* m, void* base, int rank, const cuuint64_t* gd, const cuuint64_t* gs,
              const cuuint32_t* bx, CUtensorMapSwizzle sw) {
    const cuuint32_t es[3] = {1, 1, 1};
    encode(m, CU_TENSOR_MAP_DATA_TYPE_BFLOAT16, rank, base, gd, gs, bx, es, CU_TENSOR_MAP_INTERLEAVE_NONE, sw,
           CU_TENSOR_MAP_L2_PROMOTION_NONE, CU_TENSOR_MAP_FLOAT_OOB_FILL_NONE);
}

}

extern "C" void kernel_launch(void* const* d_in, const int* in_sizes, int n_in, void* d_out, int out_size) {
    (void)in_sizes; (void)n_in; (void)out_size;
    static EncodeFn encode = nullptr;
    static void* scratch = nullptr;
    if (!encode) {
        void* fn = nullptr;
        cudaDriverEntryPointQueryResult qr;
        cudaGetDriverEntryPoint("cuTensorMapEncodeTiled", &fn, cudaEnableDefault, &qr);
        encode = (EncodeFn)fn;
        cudaGetSymbolAddress(&scratch, g_scratch);
        cudaFuncSetAttribute(fused_kernel, cudaFuncAttributeMaxDynamicSharedMemorySize, SM_TOTAL);
    }
    Maps tm;
    {
        const cuuint64_t gd[3] = {64, 8ull * 65536ull, 2}, gs[2] = {256, 128};
        const cuuint32_t bx[3] = {64, 64, 2};
        make_map(encode, &tm.k, d_in[1], 3, gd, gs, bx, CU_TENSOR_MAP_SWIZZLE_128B);
        make_map(encode, &tm.v, d_in[2], 3, gd, gs, bx, CU_TENSOR_MAP_SWIZZLE_128B);
    }
    {
        const cuuint64_t gd[2] = {4096, 512}, gs[1] = {8192};
        const cuuint32_t bx[2] = {32, 256};
        make_map(encode, &tm.wq, d_in[3], 2, gd, gs, bx, CU_TENSOR_MAP_SWIZZLE_64B);
    }
    {
        const cuuint64_t gd[3] = {64, 4096, 8}, gs[2] = {1024, 128};
        const cuuint32_t bx[3] = {64, 16, 8};
        make_map(encode, &tm.wo, d_in[4], 3, gd, gs, bx, CU_TENSOR_MAP_SWIZZLE_128B);
        const cuuint64_t gd2[3] = {64, 1792, 8};
        make_map(encode, &tm.wd, d_in[8], 3, gd2, gs, bx, CU_TENSOR_MAP_SWIZZLE_128B);
    }
    {
        const cuuint64_t gd[2] = {1792, 512}, gs[1] = {3584};
        const cuuint32_t bx[2] = {16, 256};
        make_map(encode, &tm.wg, d_in[6], 2, gd, gs, bx, CU_TENSOR_MAP_SWIZZLE_32B);
        make_map(encode, &tm.wu, d_in[7], 2, gd, gs, bx, CU_TENSOR_MAP_SWIZZLE_32B);
    }
    Params p;
    p.x = (const __nv_bfloat16*)d_in[0];
    p.k = (const char*)d_in[1];
    p.v = (const char*)d_in[2];
    p.wq = (const char*)d_in[3];
    p.wo = (const char*)d_in[4];
    p.wg = (const char*)d_in[6];
    p.wu = (const char*)d_in[7];
    p.wd = (const char*)d_in[8];
    p.out = (__nv_bfloat16*)d_out;
    p.s = (Scratch*)scratch;
    fused_kernel<<<NCTA, 256, SM_TOTAL, cudaStreamPerThread>>>(tm, p);
}
```

```cpp
#include <cuda_runtime.h>
#include <cuda_bf16.h>
#include <cuda.h>
#include <stdint.h>

namespace {

constexpr int NCTA      = 132;
constexpr int NUNIT     = 33;
constexpr int NTILE     = 1024;
constexpr int SLOT      = 16384;
constexpr int NSTAT     = 7;
constexpr int T_DYN0    = NSTAT * NUNIT;
#define NKEEP 200
#define KEEP_TAILSKIP 33
#define KRATIO 1
#define D_AR 650
#define D_SKIP 1500
#define WQ_EARLY 1
#define D_AG 100
#define D_KV 300
#define SUNROLL 1
#define MID_NPRE 2
#define S1_NPRE 2
#define MID_DPRE 0
#define ECAP 28
#define DBG_U 0
#define DBG_PH 0
constexpr int T_KEEP0   = NTILE - NKEEP;
constexpr int T_KEEPEND = NTILE - KEEP_TAILSKIP;
constexpr int SUNR      = SUNROLL;
constexpr int KEEPCAP   = 32;
constexpr unsigned SPIN_LIMIT = 1u << 22;

constexpr uint32_t SM_BASE  = 1024;
constexpr uint32_t USTR     = 2 * SLOT + 3 * 24576;
constexpr uint32_t SM_SLOTS = SM_BASE;
constexpr uint32_t SM_WG    = SM_SLOTS + 2 * USTR;
constexpr uint32_t SM_Q     = SM_WG + SLOT;
constexpr uint32_t SM_P     = SM_Q + 1024;
constexpr uint32_t SM_RED   = SM_P + 1024;
constexpr uint32_t SM_MX    = SM_RED;
constexpr uint32_t SM_BAR   = SM_RED + 192;
constexpr uint32_t SM_WBAR  = SM_BAR + 96;
constexpr uint32_t SM_TBAR  = SM_BAR + 104;
constexpr uint32_t SM_DBAR  = SM_BAR + 112;
constexpr uint32_t SM_KEEP  = SM_BAR + 128;
constexpr uint32_t SM_ST    = SM_KEEP + 128;
constexpr uint32_t SM_CMP   = SM_ST + 32;
constexpr uint32_t SM_ESC   = SM_CMP + 32;
constexpr int SM_TOTAL      = SM_ESC + 2 * ECAP * 8 - SM_BASE;
static_assert(SM_TOTAL <= 232448 && ECAP <= 32, "smem");

struct Scratch {
    uint4 part[128][8][NUNIT][2];
    uint4 ar[4][2][128][8];
    uint2 x2[256];
    uint4 q[2][2][8][128];
    unsigned ticket[2][8][32];
    unsigned done[32];
    unsigned epoch;
};
__device__ Scratch g_scratch;
#define g_s (*p.s)
#define TS(i)
#define TSD(i)
#define TSW(i)
#define TT(ph, head, tile)

struct Maps { CUtensorMap k, v, wq, wo, wg, wu, wd; };
struct Params {
    const __nv_bfloat16* x;
    const char* k;
    const char* v;
    const char* wq;
    const char* wo;
    const char* wg;
    const char* wu;
    const char* wd;
    __nv_bfloat16* out;
    Scratch* s;
};

__device__ __forceinline__ void mbar_init(uint32_t bar, uint32_t cnt) {
    asm volatile("{\n.reg .pred p;\nelect.sync _|p, 0xffffffff;\n@p mbarrier.init.shared::cta.b64 [%0], %1;\n}" ::"r"(bar), "r"(cnt) : "memory");
}
__device__ __forceinline__ void mbar_wait(uint32_t bar, uint32_t parity) {
    asm volatile("{\n.reg .pred p, q;\n.reg .u32 c;\nmov.u32 c, 0;\n"
                 "W_%=:\nmbarrier.try_wait.parity.shared::cta.b64 p, [%0], %1;\nvote.sync.all.pred p, p, 0xffffffff;\n"
                 "@p bra.uni D_%=;\nadd.u32 c, c, 1;\nsetp.lt.u32 q, c, %2;\n@q bra.uni W_%=;\ntrap;\nD_%=:\n}"
                 ::"r"(bar), "r"(parity), "n"(SPIN_LIMIT) : "memory");
}
__device__ __forceinline__ void spin_guard(uint32_t& it) {
    asm volatile("{\n.reg .pred q;\nadd.u32 %0, %0, 1;\nsetp.gt.u32 q, %0, %1;\n@q trap;\n}" : "+r"(it) : "n"(SPIN_LIMIT));
}
constexpr uint64_t POL_FIRST = 0x12f0000000000000ull, POL_NORMAL = 0x16f0000000000000ull;
__device__ __forceinline__ void tma_rows(const CUtensorMap* tm, int row, uint32_t dst, uint32_t bar) {
    asm volatile("{\n.reg .pred p;\nelect.sync _|p, 0xffffffff;\n"
                 "@p mbarrier.arrive.expect_tx.shared::cta.b64 _, [%4], %6;\n"
                 "@p cp.async.bulk.tensor.3d.shared::cluster.global.mbarrier::complete_tx::bytes.L2::cache_hint "
                 "[%0], [%1, {%2, %3, %2}], [%4], %5;\n}"
                 ::"r"(dst), "l"(tm), "r"(0), "r"(row), "r"(bar), "l"(POL_FIRST), "r"(SLOT) : "memory");
}
__device__ __forceinline__ void tma_tile(const CUtensorMap* tm, int gtile, uint32_t dst, uint32_t bar) {
    tma_rows(tm, gtile * 64, dst, bar);
}
__device__ __forceinline__ void expect_tx(uint32_t bar, uint32_t bytes) {
    asm volatile("{\n.reg .pred p;\nelect.sync _|p, 0xffffffff;\n@p mbarrier.arrive.expect_tx.shared::cta.b64 _, [%0], %1;\n}"
                 ::"r"(bar), "r"(bytes) : "memory");
}
__device__ __forceinline__ void tma_2d(const CUtensorMap* tm, int c0, int c1, uint32_t dst, uint32_t bar) {
    asm volatile("{\n.reg .pred p;\nelect.sync _|p, 0xffffffff;\n"
                 "@p cp.async.bulk.tensor.2d.shared::cluster.global.mbarrier::complete_tx::bytes.L2::cache_hint "
                 "[%0], [%1, {%2, %3}], [%4], %5;\n}"
                 ::"r"(dst), "l"(tm), "r"(c0), "r"(c1), "r"(bar), "l"(POL_FIRST) : "memory");
}
__device__ __forceinline__ void l2_prefetch(const void* p, uint32_t bytes, uint64_t pol) {
    asm volatile("{\n.reg .pred p;\nelect.sync _|p, 0xffffffff;\n"
                 "@p cp.async.bulk.prefetch.L2.global.L2::cache_hint [%0], %1, %2;\n}" ::"l"(p), "r"(bytes), "l"(pol) : "memory");
}
__device__ __forceinline__ void ldsm4(uint32_t* r, uint32_t a) {
    asm volatile("ldmatrix.sync.aligned.m8n8.x4.shared.b16 {%0,%1,%2,%3}, [%4];"
                 : "=r"(r[0]), "=r"(r[1]), "=r"(r[2]), "=r"(r[3]) : "r"(a) : "memory");
}
__device__ __forceinline__ void ldsm4t(uint32_t* r, uint32_t a) {
    asm volatile("ldmatrix.sync.aligned.m8n8.x4.trans.shared.b16 {%0,%1,%2,%3}, [%4];"
                 : "=r"(r[0]), "=r"(r[1]), "=r"(r[2]), "=r"(r[3]) : "r"(a) : "memory");
}
__device__ __forceinline__ void mma(float* c, const uint32_t* a, uint32_t b0, uint32_t b1) {
    asm volatile("mma.sync.aligned.m16n8k16.row.col.f32.bf16.bf16.f32 {%0,%1,%2,%3}, {%4,%5,%6,%7}, {%8,%9}, {%0,%1,%2,%3};"
                 : "+f"(c[0]), "+f"(c[1]), "+f"(c[2]), "+f"(c[3])
                 : "r"(a[0]), "r"(a[1]), "r"(a[2]), "r"(a[3]), "r"(b0), "r"(b1));
}
__device__ __forceinline__ uint32_t movm(uint32_t a) {
    uint32_t d; asm volatile("movmatrix.sync.aligned.m8n8.trans.b16 %0, %1;" : "=r"(d) : "r"(a)); return d;
}
__device__ __forceinline__ uint32_t pack_bf16(float lo, float hi) {
    uint32_t d; asm("cvt.rn.bf16x2.f32 %0, %1, %2;" : "=r"(d) : "f"(hi), "f"(lo)); return d;
}
__device__ __forceinline__ float bf16r(float v) { return __uint_as_float(pack_bf16(v, 0.f) << 16); }
__device__ __forceinline__ float bf_lo(uint32_t w) { return __uint_as_float(w << 16); }
__device__ __forceinline__ float bf_hi(uint32_t w) { return __uint_as_float(w & 0xffff0000u); }
__device__ __forceinline__ float ex2(float v) { float d; asm("ex2.approx.ftz.f32 %0, %1;" : "=f"(d) : "f"(v)); return d; }
__device__ __forceinline__ uint4 lds128(uint32_t a) {
    uint4 v; asm volatile("ld.shared.v4.u32 {%0,%1,%2,%3}, [%4];" : "=r"(v.x), "=r"(v.y), "=r"(v.z), "=r"(v.w) : "r"(a) : "memory"); return v;
}
__device__ __forceinline__ uint2 lds64(uint32_t a) {
    uint2 v; asm volatile("ld.shared.v2.u32 {%0,%1}, [%2];" : "=r"(v.x), "=r"(v.y) : "r"(a) : "memory"); return v;
}
__device__ __forceinline__ uint32_t lds32(uint32_t a) {
    uint32_t v; asm volatile("ld.shared.u32 %0, [%1];" : "=r"(v) : "r"(a) : "memory"); return v;
}
__device__ __forceinline__ void sts128(uint32_t a, uint32_t x, uint32_t y, uint32_t z, uint32_t w) {
    asm volatile("st.shared.v4.u32 [%0], {%1,%2,%3,%4};" ::"r"(a), "r"(x), "r"(y), "r"(z), "r"(w) : "memory");
}
__device__ __forceinline__ void sts64(uint32_t a, uint32_t x, uint32_t y) {
    asm volatile("st.shared.v2.u32 [%0], {%1,%2};" ::"r"(a), "r"(x), "r"(y) : "memory");
}
__device__ __forceinline__ void sts32(uint32_t a, uint32_t x) {
    asm volatile("st.shared.u32 [%0], %1;" ::"r"(a), "r"(x) : "memory");
}
__device__ __forceinline__ void sts16(uint32_t a, uint32_t x) {
    asm volatile("st.shared.u16 [%0], %1;" ::"r"(a), "h"((unsigned short)x) : "memory");
}
__device__ __forceinline__ uint32_t lds16(uint32_t a) {
    unsigned short v; asm volatile("ld.shared.u16 %0, [%1];" : "=h"(v) : "r"(a) : "memory"); return v;
}
__device__ __forceinline__ bool wg_bar_or(int id, bool p) {
    uint32_t r;
    asm volatile("{\n.reg .pred a, b;\nsetp.ne.u32 a, %2, 0;\nbar.red.or.pred b, %1, 128, a;\nselp.u32 %0, 1, 0, b;\n}"
                 : "=r"(r) : "r"(id), "r"((uint32_t)p) : "memory");
    return r != 0;
}
__device__ __forceinline__ uint4 ll_ld(const uint4* p) {
    unsigned long long a, b;
    asm volatile("ld.relaxed.gpu.global.v2.b64 {%0,%1}, [%2];" : "=l"(a), "=l"(b) : "l"(p) : "memory");
    return make_uint4((uint32_t)a, (uint32_t)(a >> 32), (uint32_t)b, (uint32_t)(b >> 32));
}
__device__ __forceinline__ void ll_st(uint4* p, uint32_t v0, uint32_t t0, uint32_t v1, uint32_t t1) {
    unsigned long long a = ((unsigned long long)t0 << 32) | v0, b = ((unsigned long long)t1 << 32) | v1;
    asm volatile("st.relaxed.gpu.global.v2.b64 [%0], {%1,%2};" ::"l"(p), "l"(a), "l"(b) : "memory");
}
__device__ __forceinline__ uint4 ll_ld_last(const uint4* p) {
    unsigned long long a, b;
    asm volatile("ld.relaxed.gpu.global.L2::cache_hint.v2.b64 {%0,%1}, [%2], %3;" : "=l"(a), "=l"(b) : "l"(p), "l"(POL_FIRST) : "memory");
    return make_uint4((uint32_t)a, (uint32_t)(a >> 32), (uint32_t)b, (uint32_t)(b >> 32));
}
__device__ __forceinline__ void bar_sync(int id, int n) { asm volatile("bar.sync %0, %1;" ::"r"(id), "r"(n) : "memory"); }
__device__ __forceinline__ void bar_arrive(int id, int n) { asm volatile("bar.arrive %0, %1;" ::"r"(id), "r"(n) : "memory"); }
__device__ __forceinline__ void delay_cycles(int n) {
    if (n > 0) {
        uint32_t t0, t1;
        asm volatile("mov.u32 %0, %%clock;" : "=r"(t0));
        do { asm volatile("mov.u32 %0, %%clock;" : "=r"(t1)); } while (t1 - t0 < (uint32_t)n);
    }
}
__device__ __forceinline__ int tid_now() {
    int t; asm volatile("mov.u32 %0, %%tid.x;" : "=r"(t)); return t;
}
__device__ __forceinline__ bool mbar_test(uint32_t bar, uint32_t parity) {
    uint32_t ok;
    asm volatile("{\n.reg .pred p;\nmbarrier.test_wait.parity.shared::cta.b64 p, [%1], %2;\nselp.u32 %0, 1, 0, p;\n}"
                 : "=r"(ok) : "r"(bar), "r"(parity) : "memory");
    return ok != 0;
}

struct Acc {
    float o[2][4];
    float l[4];
    float m0, m1;
};

constexpr float SCALE_LOG2 = 0.08838834764831845f * 1.4426950408889634f;

__device__ __forceinline__ void softmax_step(float* s, Acc& a, uint32_t p_wr, uint32_t mx, int barid, int lane, int wj) {
#pragma unroll
    for (int i = 0; i < 4; i++) s[i] *= SCALE_LOG2;
    bool over = fmaxf(s[0], s[2]) > a.m0 || fmaxf(s[1], s[3]) > a.m1;
    {
        uint32_t b0 = movm(pack_bf16(ex2(s[0] - a.m0), ex2(s[1] - a.m1)));
        uint32_t b1 = movm(pack_bf16(ex2(s[2] - a.m0), ex2(s[3] - a.m1)));
        if (lane < 16) sts64(p_wr, b0, b1);
    }
    if (wg_bar_or(barid, over)) {
        float x0 = fmaxf(s[0], s[2]), x1 = fmaxf(s[1], s[3]);
#pragma unroll
        for (int d = 4; d < 32; d <<= 1) {
            x0 = fmaxf(x0, __shfl_xor_sync(0xffffffffu, x0, d));
            x1 = fmaxf(x1, __shfl_xor_sync(0xffffffffu, x1, d));
        }
        if (lane < 2) sts64(mx + wj * 16 + lane * 8, __float_as_uint(x0), __float_as_uint(x1));
        wg_bar_or(barid, false);
        float n0 = a.m0, n1 = a.m1;
#pragma unroll
        for (int j = 0; j < 4; j++) {
            uint2 v = lds64(mx + j * 16 + (lane & 1) * 8);
            n0 = fmaxf(n0, __uint_as_float(v.x));
            n1 = fmaxf(n1, __uint_as_float(v.y));
        }
        float f0 = ex2(a.m0 - n0), f1 = ex2(a.m1 - n1);
        a.m0 = n0; a.m1 = n1;
        a.o[0][0] *= f0; a.o[0][2] *= f0; a.o[1][0] *= f0; a.o[1][2] *= f0; a.l[0] *= f0; a.l[2] *= f0;
        a.o[0][1] *= f1; a.o[0][3] *= f1; a.o[1][1] *= f1; a.o[1][3] *= f1; a.l[1] *= f1; a.l[3] *= f1;
        uint32_t b0 = movm(pack_bf16(ex2(s[0] - n0), ex2(s[1] - n1)));
        uint32_t b1 = movm(pack_bf16(ex2(s[2] - n0), ex2(s[3] - n1)));
        if (lane < 16) sts64(p_wr, b0, b1);
        wg_bar_or(barid, false);
    }
}

__device__ __forceinline__ uint32_t mul2(uint32_t a, uint32_t b) {
    uint32_t d; asm("mul.rn.bf16x2 %0, %1, %2;" : "=r"(d) : "r"(a), "r"(b)); return d;
}
struct Pack {
    uint32_t cmp;
    uint32_t esc;
    uint32_t key;
};
__device__ __forceinline__ void pack16(const uint32_t* a, uint32_t up, uint32_t d0, uint32_t d1, uint32_t d2, int it,
                                       const Pack& pk) {
    const uint32_t dn = 0x7f007f00u - up;
    uint32_t l[8], n[4], bad = 0;
#pragma unroll
    for (int g = 0; g < 4; g++) {
        uint32_t z[4], e = 0;
#pragma unroll
        for (int j = 0; j < 4; j++) {
            z[j] = mul2(a[4 * g + j], dn);
            e |= mul2(z[j], up) ^ a[4 * g + j];
        }
        const uint32_t x0 = __byte_perm(z[0], z[1], 0x7531), x1 = __byte_perm(z[2], z[3], 0x7531);
        l[2 * g] = __byte_perm(z[0], z[1], 0x6420);
        l[2 * g + 1] = __byte_perm(z[2], z[3], 0x6420);
        n[g] = x0 | __funnelshift_l(x1, x1, 4);
        if (e | ((x0 | x1) & 0x78787878u)) bad |= 1u << g;
        if (g & 1) sts128(g == 1 ? d0 : d1, l[2 * g - 2], l[2 * g - 1], l[2 * g], l[2 * g + 1]);
    }
    sts128(d2, n[0], n[1], n[2], n[3]);
    if (bad) {
        uint32_t i;
        asm volatile("atom.shared.add.u32 %0, [%1], %2;" : "=r"(i) : "r"(pk.cmp + 8 + (d2 >> 31)), "r"(__popc(bad)) : "memory");
#pragma unroll
        for (int g = 0; g < 4; g++) {
            asm volatile("{\n.reg .pred p, q;\n.reg .u32 a;\nsetp.ne.u32 p, %1, 0;\nsetp.lt.and.u32 q, %0, %5, p;\n"
                         "@p st.shared.v2.u32 [%6], {%7, %8};\n@p st.shared.u32 [%9], %10;\nmad.lo.u32 a, %0, 8, %2;\n"
                         "@q st.shared.v2.u32 [a], {%3, %4};\n@p add.u32 %0, %0, 1;\n}"
                         : "+r"(i)
                         : "r"(bad & (1u << g)), "r"(pk.esc), "r"(pk.key | it << 9 | g << 7), "r"(a[4 * g + 3]),
                           "n"(ECAP), "r"((g < 2 ? d0 : d1) + (g & 1) * 8), "r"(a[4 * g]), "r"(a[4 * g + 1]), "r"(d2 + g * 4),
                           "r"(a[4 * g + 2]) : "memory");
        }
    }
    __syncwarp();
}
__device__ __forceinline__ uint32_t esc_flags(const Pack& pk) {
    const uint32_t e = lds32(pk.esc + min(pk.key & 31u, ECAP - 1u) * 8);
    return __reduce_or_sync(0xffffffffu, ((e ^ pk.key) & ~0x79fu) == 0 ? 1u << ((e >> 9) & 3) : 0u);
}
__device__ __forceinline__ void unpack16(uint32_t* a, uint32_t up, uint32_t c, int it, uint32_t flags, const Pack& pk) {
    const uint4 nn = lds128(c + 4096);
    const uint4 l0 = lds128(c), l1 = lds128(c + 2048);
    const uint32_t n[4] = {nn.x, nn.y, nn.z, nn.w};
    const uint32_t l[8] = {l0.x, l0.y, l0.z, l0.w, l1.x, l1.y, l1.z, l1.w};
#pragma unroll
    for (int g = 0; g < 4; g++) {
        const uint32_t h0 = n[g] & 0x87878787u, h1 = __funnelshift_r(n[g], n[g], 4) & 0x87878787u;
        a[4 * g]     = mul2(__byte_perm(l[2 * g], h0, 0x5140), up);
        a[4 * g + 1] = mul2(__byte_perm(l[2 * g], h0, 0x7362), up);
        a[4 * g + 2] = mul2(__byte_perm(l[2 * g + 1], h1, 0x5140), up);
        a[4 * g + 3] = mul2(__byte_perm(l[2 * g + 1], h1, 0x7362), up);
    }
    if (flags >> it & 1) {
        const uint32_t me = pk.key | it << 9;
        const uint2 e = lds64(pk.esc + min(me & 31u, ECAP - 1u) * 8);
        uint32_t hit = __ballot_sync(0xffffffffu, ((e.x ^ me) & ~0x19fu) == 0) & (uint32_t)((1ull << ECAP) - 1);
#pragma unroll 1
        while (hit) {
            const int src = __ffs(hit) - 1;
            hit &= hit - 1;
            const uint32_t d = __shfl_sync(0xffffffffu, e.x, src) ^ me, v = __shfl_sync(0xffffffffu, e.y, src);
#pragma unroll
            for (int g = 0; g < 4; g++)
                asm volatile("{\n.reg .pred p;\nsetp.eq.u32 p, %4, %5;\n@p ld.shared.v2.u32 {%0, %1}, [%6];\n"
                             "@p ld.shared.u32 %2, [%7];\n@p mov.u32 %3, %8;\n}"
                             : "+r"(a[4 * g]), "+r"(a[4 * g + 1]), "+r"(a[4 * g + 2]), "+r"(a[4 * g + 3])
                             : "r"(d), "n"(g << 7), "r"(c + (g >> 1) * 2048 + (g & 1) * 8), "r"(c + 4096 + g * 4), "r"(v) : "memory");
        }
    }
}

__device__ __forceinline__ void qk_half(float* s, float* s2, const uint32_t* a, uint32_t q) {
    const uint4 q0 = lds128(q), q1 = lds128(q + 256);
    mma(s, a, q0.x, q0.y);
    mma(s2, a + 4, q0.z, q0.w);
    mma(s, a + 8, q1.x, q1.y);
    mma(s2, a + 12, q1.z, q1.w);
}
__device__ __forceinline__ void mma_ones(float* c, uint32_t b) {
    asm volatile("mma.sync.aligned.m16n8k8.row.col.f32.bf16.bf16.f32 {%0,%1,%2,%3}, {%4,%4}, {%5}, {%0,%1,%2,%3};"
                 : "+f"(c[0]), "+f"(c[1]), "+f"(c[2]), "+f"(c[3]) : "r"(0x3f803f80u), "r"(b));
}
template <bool SMALL>
__device__ __forceinline__ void pv_half(Acc& a, const uint32_t* f, uint32_t pa) {
    const uint32_t ones[4] = {0x3f803f80u, 0x3f803f80u, 0x3f803f80u, 0x3f803f80u};
    const uint4 pp = lds128(pa);
    mma(a.o[0], f, pp.x, pp.y);
    mma(a.o[1], f + 4, pp.x, pp.y);
    if (SMALL) { mma_ones(a.l, pp.x); mma_ones(a.l, pp.y); } else mma(a.l, ones, pp.x, pp.y);
    mma(a.o[0], f + 8, pp.z, pp.w);
    mma(a.o[1], f + 12, pp.z, pp.w);
    if (SMALL) { mma_ones(a.l, pp.z); mma_ones(a.l, pp.w); } else mma(a.l, ones, pp.z, pp.w);
}
__device__ __forceinline__ void load_khalf(uint32_t* a, uint32_t k) {
#pragma unroll
    for (int j = 0; j < 4; j++) ldsm4(a + j * 4, k ^ (j << 5));
    __syncwarp();
}
__device__ __forceinline__ void load_vhalf(uint32_t* f, uint32_t v) {
    ldsm4t(f, v);
    ldsm4t(f + 4, v ^ 32);
    ldsm4t(f + 8, v + 2048);
    ldsm4t(f + 12, (v ^ 32) + 2048);
    __syncwarp();
}
__device__ __forceinline__ void park(uint32_t* r, uint32_t kb, uint32_t vb) {
#pragma unroll
    for (int j = 0; j < 12; j++) {
        const int it = j / 3, c = j % 3;
        const uint32_t ad = it < 2 ? (kb ^ (c << 5)) + it * 8192 : (vb ^ ((c & 1) << 5)) + (c >> 1) * 2048 + (it - 2) * 4096;
        const uint4 u = lds128(ad);
        r[4 * j] = u.x; r[4 * j + 1] = u.y; r[4 * j + 2] = u.z; r[4 * j + 3] = u.w;
    }
}
__device__ __forceinline__ void unpark(const uint32_t* r, uint32_t c) {
#pragma unroll
    for (int j = 0; j < 12; j++) sts128(c + j * 2048, r[4 * j], r[4 * j + 1], r[4 * j + 2], r[4 * j + 3]);
}
__device__ __forceinline__ uint32_t k_offset(uint32_t slots, int wj, int lane) {
    const int row = wj * 16 + (lane & 7) + ((lane >> 3) & 1) * 8;
    return slots + row * 128 + (((lane >> 4) ^ (row & 7)) << 4);
}
__device__ __forceinline__ uint32_t v_offset(uint32_t slots, int wj, int lane) {
    const int key = (lane & 7) + (lane >> 4) * 8, cg = wj * 4 + ((lane >> 3) & 1);
    return slots + (cg >> 3) * 8192 + key * 128 + (((cg & 7) ^ (key & 7)) << 4);
}
__device__ __forceinline__ void load_kfrag(uint32_t* rk, uint32_t kb) {
#pragma unroll
    for (int ks = 0; ks < 8; ks++) ldsm4(rk + ks * 4, (kb ^ ((ks & 3) << 5)) + (ks >> 2) * 8192);
}

template <int NPRE>
__device__ __forceinline__ void ln_gemv_part(uint32_t (*f)[8], uint32_t a0, uint32_t a1, uint32_t kstride, uint32_t xw,
                                             int wq, int lane) {
    const int t = lane & 3, g = lane >> 2;
    float c0[4] = {0.f, 0.f, 0.f, 0.f}, c1[4] = {0.f, 0.f, 0.f, 0.f};
#pragma unroll
    for (int ks = 0; ks < 4; ks++) {
        uint32_t* ff = f[ks % NPRE];
        if (ks >= NPRE) {
            ldsm4t(ff, a0 + ks * kstride);
            ldsm4t(ff + 4, a1 + ks * kstride);
        }
        uint32_t xa = __shfl_sync(0xffffffffu, xw, ks * 8 + t), xb = __shfl_sync(0xffffffffu, xw, ks * 8 + 4 + t);
        if (g & 1) xa = xb = 0x3f803f80u;
        mma(c0, ff, xa, xb);
        mma(c1, ff + 4, xa, xb);
    }
    {
        const float a = bf_lo(xw), b = bf_hi(xw);
        const float su = a + b, sq = fmaf(a, a, b * b);
        float keep = (lane & 16) ? sq : su, send = (lane & 16) ? su : sq;
        keep += __shfl_xor_sync(0xffffffffu, send, 16);
#pragma unroll
        for (int k = 8; k > 0; k >>= 1) keep += __shfl_xor_sync(0xffffffffu, keep, k);
        if ((lane & 15) == 0) sts32(SM_RED + (lane >> 4) * 32 + wq * 4, __float_as_uint(keep));
    }
    float y = (t & 2) ? ((t & 1) ? c1[2] : c1[0]) : ((t & 1) ? c0[2] : c0[0]);
    float z = (t & 2) ? ((t & 1) ? c1[3] : c1[1]) : ((t & 1) ? c0[3] : c0[1]);
    sts64(SM_Q + wq * 256 + (t * 8 + g) * 8, __float_as_uint(y), __float_as_uint(z));
}
__device__ __forceinline__ float sum4(uint4 u) {
    return (__uint_as_float(u.x) + __uint_as_float(u.y)) + (__uint_as_float(u.z) + __uint_as_float(u.w));
}
__device__ __forceinline__ float ln_gemv_fin(int lane) {
    float mean, rstd;
    {
        const uint4 a = lds128(SM_RED), b = lds128(SM_RED + 16), c = lds128(SM_RED + 32), d = lds128(SM_RED + 48);
        mean = (sum4(a) + sum4(b)) * (1.f / 512.f);
        const float var = fmaxf(fmaf(sum4(c) + sum4(d), 1.f / 512.f, -mean * mean), 0.f) + 1e-5f;
        asm("rsqrt.approx.ftz.f32 %0, %1;" : "=f"(rstd) : "f"(var));
    }
    uint2 u[8];
#pragma unroll
    for (int j = 0; j < 8; j++) u[j] = lds64(SM_Q + j * 256 + lane * 8);
#define S8(f) (((__uint_as_float(u[0].f) + __uint_as_float(u[1].f)) + (__uint_as_float(u[2].f) + __uint_as_float(u[3].f))) + \
               ((__uint_as_float(u[4].f) + __uint_as_float(u[5].f)) + (__uint_as_float(u[6].f) + __uint_as_float(u[7].f))))
    return (S8(x) - mean * S8(y)) * rstd;
#undef S8
}
__device__ __forceinline__ void ar_add(uint4* dst, float y0, float y1) {
    asm volatile("red.relaxed.gpu.global.add.v4.f32 [%0], {%1, %2, %3, %1};" ::"l"(dst), "f"(1.f), "f"(y0), "f"(y1) : "memory");
}

__device__ __forceinline__ int unit_head(int cta, int wg) { return cta < 128 ? ((cta + (cta >> 3)) & 7) : (cta - 128) * 2 + wg; }
__device__ __forceinline__ int unit_index(int cta, int wg) { return cta < 128 ? (cta >> 3) * 2 + wg : 32; }
__device__ __forceinline__ void issue_item(int j, const Maps& tm, int tb, int ui, uint32_t slots, uint32_t bars) {
    const int slot = (int)((0x1010210432105432ull >> (4 * j)) & 15);
    tma_tile((j & 1) ? &tm.v : &tm.k, tb + (j >> 1) * NUNIT + ui, slots + slot * SLOT, bars + slot * 8);
}
__device__ __forceinline__ void load_ffn(const Maps& tm, int cta, int h, uint32_t z) {
    if (h) {
        tma_rows(&tm.wd, cta * 16, z, SM_WBAR);
    } else {
        expect_tx(SM_WBAR, SLOT);
        tma_2d(&tm.wu, cta * 16, 0, z, SM_WBAR);
        tma_2d(&tm.wu, cta * 16, 256, z + 8192, SM_WBAR);
    }
}
__device__ __forceinline__ void load_wq(const Maps& tm, int cta, int h, uint32_t z) {
    expect_tx(SM_WBAR, SLOT);
    tma_2d(&tm.wq, cta * 32, h * 256, z, SM_WBAR);
}
__device__ __forceinline__ void draw_ticket(uint32_t& ticket, const Params& p, int ph, int head, int lane) {
    asm volatile("{\n.reg .pred p;\nsetp.eq.u32 p, %2, 0;\n@p atom.relaxed.gpu.global.inc.u32 %0, [%1], 0xfffffffe;\n}"
                 : "+r"(ticket) : "l"(&g_s.ticket[ph][head][0]), "r"(lane) : "memory");
}
#define DESC(sk, sv) ((uint32_t)((sk) | ((sv) << 3) | 64))

__device__ __forceinline__ uint4* part_dst(const Params& p, int head, int ui, int tid) {
    const int lane = tid & 31, g = lane >> 2, t = lane & 3;
    return &g_s.part[(head * 4 + 2 * (t & 1) + (t >> 1)) * 4 + ((tid >> 5) & 3)][g >> 1][ui][g & 1];
}
__device__ __forceinline__ uint4* q_dst(const Params& p, int layer, int cta, int lane) {
    return &g_s.q[layer][(lane >> 3) & 1][cta >> 4][((cta & 3) * 16 + ((cta >> 2) & 3) * 4) * 2 + (lane & 7)];
}
__device__ __forceinline__ void publish_q(uint4* out, float r, uint32_t tag, int lane) {
    const int src = (lane & 1) * 16 + ((lane >> 1) & 3) * 2;
    const float q0 = __shfl_sync(0xffffffffu, r, src), q1 = __shfl_sync(0xffffffffu, r, src + 1);
    const float q2 = __shfl_sync(0xffffffffu, r, src + 8), q3 = __shfl_sync(0xffffffffu, r, src + 9);
    if (lane < 16) ll_st(out, pack_bf16(q0, q1), tag, pack_bf16(q2, q3), tag);
}

template <bool TAIL>
__device__ __forceinline__ void gemv_chain(const Maps& tm, const Params& p, const int cta, const uint32_t tag) {
    constexpr uint32_t Z_WO = SM_SLOTS + (TAIL ? 2 : 0) * SLOT, Z_GU = SM_SLOTS + (TAIL ? 3 : 0) * SLOT;
    [[maybe_unused]] constexpr int TB = TAIL ? 16 : 0;
    const int wq = __shfl_sync(0xffffffffu, tid_now() >> 5, 0);
    uint32_t xo;
    {
        const int lane = tid_now() & 31, g = lane >> 2, t = lane & 3;
        if (!TAIL) {
            const unsigned short* xp = reinterpret_cast<const unsigned short*>(p.x) + wq * 64 + t * 16 + g;
            xo = xp[0] | (uint32_t)xp[8] << 16;
            if (wq == 0 && lane < 16) ll_st(q_dst(p, 1, cta, lane), 0, 0, 0, 0);
            __syncwarp();
            if (wq == 1) l2_prefetch(&g_s.ar[0][0][0][0] + (cta & 63) * 128, 2048, POL_NORMAL);
        } else {
            unsigned long long u;
            uint32_t it = 0;
            do {
                spin_guard(it);
                asm volatile("ld.relaxed.gpu.global.b64 %0, [%1];" : "=l"(u) : "l"(&g_s.x2[wq * 32 + lane]) : "memory");
            } while (__any_sync(0xffffffffu, (uint32_t)(u >> 32) != tag - 1));
            xo = (uint32_t)u;
        }
        const uint32_t t16 = tag & 0xffffu;
        const uint4* src = &g_s.part[cta][wq][lane & 15][lane >> 4];
        const bool three = (lane & 15) == 0;
        if (wq == 0) {
            const uint32_t target = ((tag >> 2) * 2 + (TAIL ? 2 : 1)) * (2 * NCTA);
            uint32_t it = 0;
            while (true) {
                uint32_t v;
                asm volatile("ld.acquire.gpu.global.u32 %0, [%1];" : "=r"(v) : "l"(&g_s.done[0]) : "memory");
                const int rem = __shfl_sync(0xffffffffu, (int)(target - v), 0);
                if (rem <= 0) break;
                spin_guard(it);
                if (rem > 16) delay_cycles(400);
            }
        }
        __syncthreads();
        TS(TB + 14);
        uint4 a = ll_ld_last(src), b = ll_ld_last(src + 32), e = make_uint4(0, 0xff800000u | t16, 0, t16);
        if (three) e = ll_ld_last(src + 64);
        const uint32_t wa0 = Z_WO + wq * 2048 + ((lane & 7) + (lane >> 4) * 8) * 128 + ((((lane >> 3) & 1) ^ (lane & 7)) << 4);
        uint32_t f0[4][4], f1[4][4];
        mbar_wait(TAIL ? SM_TBAR : SM_WBAR, TAIL ? 0 : 1);
        if (TAIL) {
#pragma unroll
            for (int mt = 0; mt < 4; mt++) {
                ldsm4t(f0[mt], wa0 ^ (mt << 5));
                ldsm4t(f1[mt], (wa0 ^ (mt << 5)) + USTR);
            }
        }
        {
            uint32_t it = 0;
            while (__any_sync(0xffffffffu, ((a.y ^ t16) | (a.w ^ t16) | (b.y ^ t16) | (b.w ^ t16) | (e.y ^ t16) | (e.w ^ t16)) << 16 != 0)) {
                spin_guard(it);
                a = ll_ld_last(src);
                b = ll_ld_last(src + 32);
                if (three) e = ll_ld_last(src + 64);
            }
        }
        TS(TB + 0);
        if (!TAIL && wq >= 6) l2_prefetch((wq == 6 ? p.wu : p.wd) + (size_t)cta * 14336, 14336, POL_FIRST);
        const float la = __uint_as_float(__byte_perm(a.w, a.y, 0x7632)), lb = __uint_as_float(__byte_perm(b.w, b.y, 0x7632));
        const float le = __uint_as_float(__byte_perm(e.w, e.y, 0x7632));
        float mm;
        {
            int k = __float_as_int(fmaxf(fmaxf(la, lb), le));
            k ^= (k >> 31) & 0x7fffffff;
            k = __reduce_max_sync(0xffffffffu, k);
            k ^= (k >> 31) & 0x7fffffff;
            mm = __int_as_float(k);
        }
        const float wa = ex2(la - mm), wb = ex2(lb - mm), we = ex2(le - mm);
        const float v0 = fmaf(we, __uint_as_float(e.x), fmaf(wb, __uint_as_float(b.x), wa * __uint_as_float(a.x)));
        const float v1 = fmaf(we, __uint_as_float(e.z), fmaf(wb, __uint_as_float(b.z), wa * __uint_as_float(a.z)));
        float ws = wa + wb + we;
        float kk = (lane & 8) ? v1 : v0;
        kk += __shfl_xor_sync(0xffffffffu, (lane & 8) ? v0 : v1, 8);
        ws += __shfl_xor_sync(0xffffffffu, ws, 8);
        if (!TAIL) {
#pragma unroll
            for (int mt = 0; mt < S1_NPRE; mt++) {
                ldsm4t(f0[mt], wa0 ^ (mt << 5));
                ldsm4t(f1[mt], (wa0 ^ (mt << 5)) + USTR);
            }
        }
#pragma unroll
        for (int k = 4; k > 0; k >>= 1) {
            kk += __shfl_xor_sync(0xffffffffu, kk, k);
            ws += __shfl_xor_sync(0xffffffffu, ws, k);
        }
        {
            float r; asm("rcp.approx.ftz.f32 %0, %1;" : "=f"(r) : "f"(ws));
            const uint32_t o = pack_bf16(kk * r, 0.f);
            if ((lane & 7) == 0) sts16(SM_RED + 128 + (wq & 3) * 16 + (wq >> 2) * 8 + ((lane >> 3) & 1) * 4 + (lane >> 4) * 2, o);
        }
        uint4* out = &g_s.ar[TAIL ? 2 : 0][cta & 1][wq * 16 + (lane >> 1)][lane & 1];
        __syncthreads();
        TS(TB + 1);
        const uint4 ob = lds128(SM_RED + 128 + t * 16);
        float c0[4] = {0.f, 0.f, 0.f, 0.f}, c1[4] = {0.f, 0.f, 0.f, 0.f};
#pragma unroll
        for (int mt = 0; mt < 4; mt++) {
            constexpr int NP = TAIL ? 4 : S1_NPRE;
            uint32_t* g0 = f0[mt % NP];
            uint32_t* g1 = f1[mt % NP];
            if (mt >= NP) {
                ldsm4t(g0, wa0 ^ (mt << 5));
                ldsm4t(g1, (wa0 ^ (mt << 5)) + USTR);
            }
            const bool mine = (g >> 1) == mt;
            mma(c0, g0, mine ? ob.x : 0u, mine ? ob.y : 0u);
            mma(c1, g1, mine ? ob.z : 0u, mine ? ob.w : 0u);
        }
        ar_add(out, c0[0] + c1[0], c0[2] + c1[2]);
        TS(TB + 2);
        if (!TAIL) {
            if (wq == 4 || wq == 5) bar_sync(4, 256); else bar_arrive(4, 256);
        }
    }
#pragma unroll 1
    for (int hv = 0; hv < 2; hv++) {
        const int half = __shfl_sync(0xffffffffu, hv, 0);
        const bool ffn = cta < 112;
        if (TAIL && (half ? cta != 0 : !ffn)) break;
        uint32_t t0;
        asm volatile("mov.u32 %0, %%clock;" : "=r"(t0));
        const int lane = tid_now() & 31, g = lane >> 2, t = lane & 3;
        const bool qs = !TAIL && half;
        [[maybe_unused]] const int h = wq - 4;
        [[maybe_unused]] const uint32_t z = SM_SLOTS + h * USTR;
        if (!TAIL && (wq == 4 || wq == 5)) {
            if (!half) {
                if (ffn) load_ffn(tm, cta, h, z);
            } else if (!(WQ_EARLY && ffn && h == 0)) {
                if (!ffn) delay_cycles(D_SKIP);
                load_wq(tm, cta, h, z);
            }
        }
        if (!TAIL && !half && wq >= 6) l2_prefetch(p.wq + (size_t)(cta + (wq - 6) * 128) * 16384, 16384, POL_FIRST);
        constexpr int NPRE = TAIL ? 4 : MID_NPRE;
        uint32_t f[NPRE][8];
        const int row = (wq & 3) * 64 + (lane & 7) + (lane >> 4) * 8;
        const uint32_t a0 = qs ? SM_SLOTS + (wq >> 2) * USTR + row * 64 + ((((lane >> 3) & 1) ^ ((lane >> 1) & 3)) << 4)
                               : SM_WG + (wq >> 2) * 8192 + row * 32 + ((((lane >> 3) ^ (lane >> 2)) & 1) << 4);
        const uint32_t a1 = qs ? a0 ^ 32 : a0 - (SM_WG - Z_GU), kstride = qs ? 1024 : 512;
        {
            const uint4* src = &g_s.ar[(TAIL ? 2 : 0) + half][0][wq * 16 + (lane >> 1)][lane & 1];
            const uint32_t cnt = __float_as_uint(half ? 56.f : 64.f);
            if (TAIL && !half) {
                mbar_wait(SM_WBAR, 0);
#pragma unroll
                for (int ks = 0; ks < NPRE; ks++) {
                    ldsm4t(f[ks], a0 + ks * kstride);
                    ldsm4t(f[ks] + 4, a1 + ks * kstride);
                }
            }
            {
                const uint32_t d = (half && !ffn) ? D_AR + D_SKIP : D_AR;
                uint32_t t1;
                do { asm volatile("mov.u32 %0, %%clock;" : "=r"(t1)); } while (t1 - t0 < d);
            }
            uint4 u, v;
            uint32_t it = 0;
            do {
                spin_guard(it);
                u = ll_ld(src);
                v = ll_ld(src + 1024);
            } while (__any_sync(0xffffffffu, u.x != cnt || u.w != cnt || v.x != cnt || v.w != cnt));
            const uint32_t y = pack_bf16(__uint_as_float(u.y) + __uint_as_float(v.y), __uint_as_float(u.z) + __uint_as_float(v.z));
            xo = pack_bf16(bf_lo(xo) + bf_lo(y), bf_hi(xo) + bf_hi(y));
        }
        if (half) TS(TB + 7); else TS(TB + 3);
        if (!half && !ffn) continue;
        const uint32_t xw = movm(xo);
        if (TAIL && half) {
            reinterpret_cast<uint32_t*>(p.out)[wq * 32 + lane] = xw;
            if (wq == 0) {
                if (lane < 16) g_s.ticket[lane >> 3][lane & 7][0] = 0;
                if (lane == 16) g_s.epoch = (tag >> 2) + 1;
            }
            break;
        }
        if (!TAIL) {
            mbar_wait(SM_WBAR, qs && ffn);
#pragma unroll
            for (int ks = 0; ks < NPRE; ks++) {
                ldsm4t(f[ks], a0 + ks * kstride);
                ldsm4t(f[ks] + 4, a1 + ks * kstride);
            }
        }
        if (half) TS(8); else TS(TB + 4);
        ln_gemv_part<NPRE>(f, a0, a1, kstride, xw, wq, lane);
        const uint32_t wd0 = Z_GU + USTR + wq * 2048 + ((lane & 7) + (lane >> 4) * 8) * 128 + ((((lane >> 3) & 1) ^ (lane & 7)) << 4);
        uint32_t d[4][4];
        constexpr int DPRE = TAIL ? 4 : MID_DPRE;
#pragma unroll
        for (int mt = 0; mt < DPRE; mt++) ldsm4t(d[mt], wd0 ^ (mt << 5));
        uint4* out = qs ? q_dst(p, 1, cta, lane) : &g_s.ar[TAIL ? 3 : 1][cta & 1][wq * 16 + (lane >> 1)][lane & 1];
        __syncthreads();
        if (!half) TS(TB + 5);
        if (WQ_EARLY && !TAIL && !half && wq == 4) load_wq(tm, cta, 0, z);
        float r = ln_gemv_fin(lane);
        if (qs) {
            if (wq == 0) publish_q(out, r, tag, lane);
            if (cta == 0)
                asm volatile("st.relaxed.gpu.global.b64 [%0], %1;" ::"l"(&g_s.x2[wq * 32 + lane]), "l"((unsigned long long)tag << 32 | xo) : "memory");
            __syncthreads();
            TS(9);
            break;
        }
        r = bf16r(r);
        const float up = __shfl_down_sync(0xffffffffu, r, 16);
#pragma unroll
        for (int mt = DPRE; mt < 4; mt++) ldsm4t(d[mt], wd0 ^ (mt << 5));
        const float hh = (r > 0.f ? r : 0.f * r) * up;
        const float h0 = __shfl_sync(0xffffffffu, hh, 2 * t), h1 = __shfl_sync(0xffffffffu, hh, 2 * t + 1);
        const float h2 = __shfl_sync(0xffffffffu, hh, 2 * t + 8), h3 = __shfl_sync(0xffffffffu, hh, 2 * t + 9);
        const uint32_t b0 = pack_bf16(h0, h1), b1 = pack_bf16(h2, h3);
        float c0[4] = {0.f, 0.f, 0.f, 0.f}, c1[4] = {0.f, 0.f, 0.f, 0.f};
#pragma unroll
        for (int mt = 0; mt < 4; mt++) {
            const bool mine = (g >> 1) == mt;
            mma((mt & 1) ? c1 : c0, d[mt], mine ? b0 : 0u, mine ? b1 : 0u);
        }
        ar_add(out, c0[0] + c1[0], c0[2] + c1[2]);
        TS(TB + 6);
        if (!TAIL) {
            if (wq == 4 || wq == 5) bar_sync(4, 256); else bar_arrive(4, 256);
        }
    }
}

#define UVARS                                                                                               \
    const int wqu = __shfl_sync(0xffffffffu, tid_now() >> 5, 0);                                            \
    const int wg = wqu >> 2, wj = wqu & 3;                                                                  \
    [[maybe_unused]] const int head = unit_head(cta, wg), ui = unit_index(cta, wg), tb = head * NTILE;      \
    [[maybe_unused]] const uint32_t slots = SM_SLOTS + wg * USTR, bars = SM_BAR + wg * 48;                  \
    [[maybe_unused]] const int barid = 1 + wg;                                                              \
    [[maybe_unused]] const uint32_t qbase = cta < 128 ? SM_Q : SM_WG + wg * 1024;                           \
    [[maybe_unused]] const uint32_t rec = SM_ST + wg * 16;                                                  \
    [[maybe_unused]] const uint32_t mx = SM_MX + wg * 64;
#define Q_RD (qbase + (lane & 15) * 16)
#define P_RD (SM_P + wg * 512 + (lane & 15) * 16)
#define P_WR (SM_P + wg * 512 + (wj >> 1) * 256 + (wj & 1) * 8 + (lane & 15) * 16)

__device__ __forceinline__ void static_phase(const Maps& tm, const int cta, Acc& acc, uint32_t (*rp)[48]) {
    UVARS
#pragma unroll 1
    for (int rv = 0; rv < NSTAT; rv++) {
        const int rn = __shfl_sync(0xffffffffu, rv, 0);
        const int lane = tid_now() & 31;
        const uint32_t d = (uint32_t)(0x10210432105432ull >> (8 * rn)), par = 0x7c0u >> (2 * rn);
        const int sk = d & 7, sv = (d >> 4) & 7;
        Pack pk;
        pk.cmp = SM_CMP + wg * 16;
        pk.esc = SM_ESC + wg * (ECAP * 8);
        pk.key = (rn < 4 ? rn + 3 : 6 - rn) << 11 | wj << 5 | lane;
        const bool inplace = rn < 4;
        uint32_t dst = slots + 2 * SLOT + (6 - rn) * 24576 + (wj * 32 + lane) * 16;
        uint32_t kb = k_offset(slots, wj, lane) + sk * SLOT;
        float s[4] = {0.f, 0.f, 0.f, 0.f}, s2[4] = {0.f, 0.f, 0.f, 0.f};
        uint32_t a[16];
        mbar_wait(bars + sk * 8, par & 1);
        {
            const uint32_t b4 = lds32(pk.cmp);
#pragma unroll SUNR
            for (int hv = 0; hv < 2; hv++) {
                const int h = __shfl_sync(0xffffffffu, hv, 0);
                load_khalf(a, kb);
                pack16(a, b4, inplace ? kb : dst, inplace ? kb ^ 32 : dst + 2048, inplace ? kb ^ 64 : dst + 4096, h, pk);
                qk_half(s, s2, a, Q_RD + h * 512);
                kb += 8192; dst += 6144;
            }
        }
#pragma unroll
        for (int i = 0; i < 4; i++) s[i] += s2[i];
        softmax_step(s, acc, P_WR, mx, barid, lane, wj);
        uint32_t vb = v_offset(slots, wj, lane) + sv * SLOT;
        mbar_wait(bars + sv * 8, (par >> 1) & 1);
        {
            const uint32_t b4 = lds32(pk.cmp + 4);
#pragma unroll SUNR
            for (int yv = 0; yv < 2; yv++) {
                const int y = __shfl_sync(0xffffffffu, yv, 0);
                load_vhalf(a, vb);
                pack16(a, b4, inplace ? vb : dst, inplace ? vb ^ 32 : dst + 2048, inplace ? vb + 2048 : dst + 4096, 2 + y, pk);
                pv_half<true>(acc, a, SM_P + wg * 512 + (tid_now() & 15) * 16 + y * 256);
                vb += 4096; dst += 6144;
            }
            vb -= 8192;
        }
        {
            const uint32_t kb2 = k_offset(slots, wj, tid_now() & 31) + sk * SLOT;
            if (rn == 0) park(rp[0], kb2, vb);
            if (rn == 1) park(rp[1], kb2, vb);
            if (rn == 2) park(rp[2], kb2, vb);
            if (rn == 3) park(rp[3], kb2, vb);
        }
        asm volatile("fence.proxy.async.shared::cta;" ::: "memory");
        wg_bar_or(barid, false);
        const int j = (int)((wj == 1 ? 0xe0c0a86u : 0xfd0b907u) >> (4 * rn)) & 15;
        if ((wj == 1 || wj == 2) && j) issue_item(j, tm, tb, ui, slots, bars);
        if (wj == 0) {
            const uint32_t st = lds32(rec + 4);
            if (lane == 0 && lds32(pk.cmp + 8) > ECAP) {
                sts16(SM_KEEP + wg * 64 + (st & 255) * 2, rn * NUNIT + ui);
                sts32(rec + 4, (st + 1) | 0x10000u << (pk.key >> 11));
            }
            __syncwarp();
        }
    }
    TSD(28);
    {
        uint32_t c = slots + 2 * SLOT + 12288 + (tid_now() & 127) * 16;
#pragma unroll 1
        for (int j = 0; j < 6; j++, c += 2048) {
            const uint4 u = lds128(c), v = lds128(c + 36864);
            sts128(c, v.x, v.y, v.z, v.w);
            sts128(c + 36864, u.x, u.y, u.z, u.w);
        }
        asm volatile("fence.proxy.async.shared::cta;" ::: "memory");
    }
    if (wqu == 0) __threadfence();
    wg_bar_or(barid, false);
}

__device__ __forceinline__ void acc_init(Acc& a) {
#pragma unroll
    for (int i = 0; i < 4; i++) { a.o[0][i] = 0.f; a.o[1][i] = 0.f; a.l[i] = 0.f; }
    a.m0 = a.m1 = __int_as_float(0xff800000);
}

__device__ __forceinline__ void attention_pass(const Maps& tm, const Params& p, const int cta, const int ph, const uint32_t tag0,
                                               Acc& acc, uint32_t (*rp)[48], float* s) {
    UVARS
    const int lim = ph ? T_KEEP0 : NTILE;
    uint32_t ticket = 0;
    if (wj == 0) draw_ticket(ticket, p, ph, head, tid_now() & 31);
    const uint32_t st0 = __shfl_sync(0xffffffffu, lds32(rec + 4), 0);
    uint32_t phbits = __shfl_sync(0xffffffffu, lds32(rec + 12), 0);
    int nk = st0 & 255;
    uint32_t cur = DESC(0, 1) | 256;
    uint32_t q0 = 0, q1 = 0;
    int rn = NSTAT, ki = 0, since = KRATIO;
    bool open = true;
    if (ph) {
        rn = 0; q0 = DESC(0, 3) | 256; cur = DESC(2, 1) | 128;
        if (nk > 0 && __shfl_sync(0xffffffffu, (int)lds16(SM_KEEP + wg * 64 + nk * 2 - 2), 0) >= T_KEEP0) nk--;
        else cur |= 512;
    }
#pragma unroll 1
    while (true) {
        const int lane = tid_now() & 31;
        const int sk = cur & 7, sv = (cur >> 3) & 7;
        const bool keeps = ph && ki < nk && cur;
        const bool want = cur && open && (!(q0 & 256) || (keeps && since < KRATIO));
        int tkeep = 0;
        if (keeps) tkeep = __shfl_sync(0xffffffffu, lds16(SM_KEEP + wg * 64 + ki * 2), 0);
        const bool resid = rn + (cur == 0) < NSTAT;
        if (cur ? !(cur & 512) : !(st0 >> (16 + rn) & 1)) {
            Pack pk;
            pk.cmp = SM_CMP + wg * 16;
            pk.esc = SM_ESC + wg * (ECAP * 8);
            pk.key = rn << 11 | wj << 5 | lane;
            uint32_t a[16], vb, flags = 0;
            if (cur) {
                vb = v_offset(slots, wj, lane) + sv * SLOT;
                if (!(cur & 128)) {
                    const uint32_t kb = k_offset(slots, wj, lane) + sk * SLOT;
                    float s2[4] = {0.f, 0.f, 0.f, 0.f};
                    s[0] = s[1] = s[2] = s[3] = 0.f;
                    mbar_wait(bars + sk * 8, (phbits >> sk) & 1);
                    if (DBG_U && ph == DBG_PH) TSW(26);
                    load_khalf(a, kb);
                    qk_half(s, s2, a, Q_RD);
                    load_khalf(a, kb + 8192);
                    qk_half(s, s2, a, Q_RD + 512);
                    mbar_wait(bars + sv * 8, (phbits >> sv) & 1);
                    phbits ^= 1u << sk | 1u << sv;
#pragma unroll
                    for (int i = 0; i < 4; i++) s[i] += s2[i];
                }
                load_vhalf(a, vb);
            } else {
                vb = slots + 2 * SLOT + (wj * 32 + lane) * 16;
                flags = esc_flags(pk);
                if (rn < 3) {
                    const uint4 u = lds128(((vb & ~32u) | (rn & 1) << 5) + 32768 + (rn >> 1) * 2048);
                    s[0] = __uint_as_float(u.x); s[1] = __uint_as_float(u.y); s[2] = __uint_as_float(u.z); s[3] = __uint_as_float(u.w);
                    vb += ((0x423 >> (4 * rn)) & 7) * 12288;
                } else {
                    vb += 49152;
                    if (rn == 3) unpark(rp[0], vb);
                    if (rn == 4) unpark(rp[1], vb);
                    if (rn == 5) unpark(rp[2], vb);
                    if (rn == 6) unpark(rp[3], vb);
                    const uint32_t up = lds32(pk.cmp);
                    float s2[4] = {0.f, 0.f, 0.f, 0.f};
                    s[0] = s[1] = s[2] = s[3] = 0.f;
#pragma unroll 1
                    for (int h = 0; h < 2; h++) {
                        unpack16(a, up, vb + h * 6144, h, flags, pk);
                        qk_half(s, s2, a, Q_RD + h * 512);
                    }
#pragma unroll
                    for (int i = 0; i < 4; i++) s[i] += s2[i];
                }
                unpack16(a, lds32(pk.cmp + 4), vb + 12288, 2, flags, pk);
            }
            softmax_step(s, acc, P_WR, mx, barid, lane, wj);
            pv_half<false>(acc, a, P_RD);
            if (cur) load_vhalf(a, vb + 4096);
            else unpack16(a, lds32(pk.cmp + 4), vb + 18432, 3, flags, pk);
            pv_half<false>(acc, a, P_RD + 256);
        } else {
            wg_bar_or(barid, false);
        }
        if (wj == 0)
            asm volatile("{\n.reg .pred p, q;\n.reg .u32 w;\nmov.u32 w, %6;\nsetp.eq.u32 p, %7, 0;\n@p bra.uni N_%=;\n"
                         "shfl.sync.idx.b32 w, %1, 0, 31, 0xffffffff;\nadd.u32 w, w, %5;\nmin.u32 w, w, %6;\nN_%=:\n"
                         "setp.eq.u32 p, %2, 0;\nsetp.ge.and.u32 q, w, %3, p;\n@q or.b32 w, w, 0x10000;\n"
                         "@p st.shared.u32 [%0], w;\n@q red.relaxed.gpu.global.add.u32 [%4], 1;\n}"
                         ::"r"(rec), "r"(ticket), "r"(lane), "r"((!resid && !q0 && !keeps) ? lim : NTILE + 1),
                           "l"(&g_s.done[lane]), "n"(T_DYN0 + NUNIT), "n"(NTILE), "r"((uint32_t)want) : "memory");
        bar_sync(8 + wg, 128);
        int tv = __shfl_sync(0xffffffffu, (int)lds32(rec), 0);
        if (tv > NTILE) break;
        if (cur == 0) rn++;
        uint32_t push = 0;
        const bool streamed = tv < lim;
        if (streamed) push = (cur & 127) | 256;
        else if (keeps) { tv = tkeep; push = cur & 127; }
        if (push && (wj == 1 || wj == 2)) {
            const int sl = wj == 1 ? sk : sv;
            tma_tile(wj == 1 ? &tm.k : &tm.v, tb + tv, slots + sl * SLOT, bars + sl * 8);
            if (!ph && tv >= T_KEEP0 && tv < T_KEEPEND) l2_prefetch((wj == 1 ? p.k : p.v) + (size_t)(tb + tv) * SLOT, SLOT, POL_NORMAL);
        }
        if (streamed) {
            since++;

            if (!ph && tv >= T_KEEP0) {
                if (wj == 3 && lane == 0) sts16(SM_KEEP + wg * 64 + nk * 2, tv);
                nk++;
                if (nk >= KEEPCAP) open = false;
            }
            if (open && wj == 0) draw_ticket(ticket, p, ph, head, lane);
        } else {
            if (want) open = false;
            if (keeps) { ki++; since = 0; }
        }
        if (q0) q1 |= push; else q0 = push;
        if (resid && (q0 == 0 || (streamed && q1 == 0))) {
            cur = 0;
        } else {
            cur = q0; q0 = q1; q1 = 0;
        }
    }
    const int lane = tid_now() & 31;
    {
        const int e = (lane >> 1) & 1;
        float l = e ? acc.l[1] : acc.l[0], m = e ? acc.m1 : acc.m0;
        float inv; asm("rcp.approx.ftz.f32 %0, %1;" : "=f"(inv) : "f"(l));
        float lg; asm("lg2.approx.ftz.f32 %0, %1;" : "=f"(lg) : "f"(l));
        uint32_t lam = __float_as_uint(m + lg);
        const uint32_t t16 = (tag0 + ph + 1) & 0xffffu;
        uint32_t ta = (lam & 0xffff0000u) | t16, tc = (lam << 16) | t16;
        uint4* dst = part_dst(p, head, ui, wqu * 32 + lane);
        ll_st(dst, __float_as_uint((e ? acc.o[0][1] : acc.o[0][0]) * inv), ta,
                   __float_as_uint((e ? acc.o[0][3] : acc.o[0][2]) * inv), tc);
        ll_st(dst + 4 * NUNIT * 2, __float_as_uint((e ? acc.o[1][1] : acc.o[1][0]) * inv), ta,
                                   __float_as_uint((e ? acc.o[1][3] : acc.o[1][2]) * inv), tc);
    }
    if (ph) TSW(38); else TSW(36);
    if (wj == 0 && lane == 0) {
        sts32(rec + 4, nk | (st0 & 0xffff0000u));
        sts32(rec + 12, phbits);
    }
}

__global__ void __launch_bounds__(256, 1)
fused_kernel(const __grid_constant__ Maps tm, const Params p) {
    extern __shared__ __align__(1024) unsigned char smem_raw[];
    const int cta = blockIdx.x;
    const bool worker = cta < 128;
    uint32_t tag0;
    if ((uint32_t)__cvta_generic_to_shared(smem_raw) != SM_BASE) __trap();
    TS(40);
    uint32_t rp[4][48];
    Acc acc;
    {
        UVARS
        const int lane = tid_now() & 31;
        if (wj == 1 && worker) l2_prefetch(p.wq + (size_t)(cta * 2 + wg) * SLOT, SLOT, POL_NORMAL);
        if (wj == 0) {
#pragma unroll
            for (int i = 0; i < 6; i++) mbar_init(bars + i * 8, 1);
            mbar_init(SM_WBAR + wg * 8, 2);
            mbar_init(SM_DBAR + wg * 8, 1);
            asm volatile("fence.proxy.async.shared::cta;" ::: "memory");
            __syncwarp();
            if (worker && wg == 0) {
                load_wq(tm, cta, 0, SM_SLOTS + SLOT);
                load_wq(tm, cta, 1, SM_SLOTS + USTR + SLOT);
            }
            delay_cycles(D_KV);
            issue_item(0, tm, tb, ui, slots, bars);
            issue_item(1, tm, tb, ui, slots, bars);
            if (worker && wg == 0 && lane < 16) ll_st(q_dst(p, 0, cta, lane), 0, 0, 0, 0);
        }
        if (wj == 1) {
            if (lane < ECAP) sts64(SM_ESC + wg * (ECAP * 8) + lane * 8, 0xffffffffu, 0);
            if (lane < 2) sts128(rec + lane * 32, 0, 0, 0, 0x27);
        }
        if (wj == 2) {
            const uint4 u = *reinterpret_cast<const uint4*>(p.x + wg * 256 + lane * 8);
            sts128(SM_P + wg * 512 + lane * 16, u.x, u.y, u.z, u.w);
        }
        if (wqu == 7 && worker && lane < 16) ll_st(&g_s.ar[0][0][0][0] + (cta * 8 + (lane >> 1)) * 8 + (lane & 1), 0, 0, 0, 0);
        if (wqu == 3) {
            uint32_t e;
            asm volatile("ld.relaxed.gpu.global.u32 %0, [%1];" : "=r"(e) : "l"(&g_s.epoch) : "memory");
            sts32(SM_RED, e * 4 + 1);
        }
        __syncthreads();
        tag0 = __shfl_sync(0xffffffffu, lds32(SM_RED), 0);
        const uint32_t xw = lds32(SM_P + wqu * 128 + lane * 4);
        __syncthreads();
        uint32_t it = 0;
        int item = 2;
#pragma unroll 1
        for (int stage = worker ? 0 : 1; stage < 3 || item < 6;) {
            if (item < (stage ? 6 : 5) && (wj != 1 || stage == 3 || mbar_test(bars + item * 8, 0))) {
                if (wj == 1) issue_item(item, tm, tb, ui, slots, bars);
                item++;
                continue;
            }
            spin_guard(it);
            if (stage == 0) {
                if (!mbar_test(SM_WBAR, 0)) continue;
                TS(32);
                const int row = wj * 64 + (lane & 7) + (lane >> 4) * 8;
                const uint32_t a0 = slots + SLOT + row * 64 + ((((lane >> 3) & 1) ^ ((lane >> 1) & 3)) << 4);
                uint32_t f[1][8];
                ldsm4t(f[0], a0);
                ldsm4t(f[0] + 4, a0 ^ 32);
                ln_gemv_part<1>(f, a0, a0 ^ 32, 1024, xw, wqu, lane);
                __syncthreads();
                if (wqu == 0) publish_q(q_dst(p, 0, cta, lane), ln_gemv_fin(lane), tag0, lane);
                if (wqu == 6 && cta < 112) {
                    expect_tx(SM_DBAR, SLOT);
                    tma_2d(&tm.wg, cta * 16, 0, SM_WG, SM_DBAR);
                    tma_2d(&tm.wg, cta * 16, 256, SM_WG + 8192, SM_DBAR);
                }
                __syncthreads();
                TS(33);
            } else if (stage == 1) {
                if (!mbar_test(bars + 2 * 8, 0) || !mbar_test(bars + 3 * 8, 0)) continue;
#pragma unroll 1
                for (int h = 0; h < 4; h++) {
                    uint32_t r[16], m = 0;
                    load_khalf(r, k_offset(slots, wj, lane) + 2 * SLOT + h * 8192);
#pragma unroll
                    for (int j = 0; j < 16; j++) m = __vmaxu2(m, r[j] & 0x7fff7fffu);
                    m = __reduce_max_sync(0xffffffffu, max(m >> 23, (m >> 7) & 0xffu));
                    if (lane == 0)
                        asm volatile("red.shared.max.u32 [%0], %1;" ::"r"(SM_CMP + wg * 16 + (h & 2) * 2),
                                     "r"((min(max(m, 15u), 141u) + 112u) * 0x00800080u) : "memory");
                    __syncwarp();
                }
            } else {
                const uint4 v = ll_ld(&g_s.q[0][cta >> 7][head][wj * 32 + lane]);
                if (__any_sync(0xffffffffu, v.y != tag0 || v.w != tag0)) { delay_cycles(200); continue; }
                sts64(qbase + (wj * 32 + lane) * 8, v.x, v.z);
            }
            stage++;
        }
        wg_bar_or(barid, false);
        TS(34);
#pragma unroll
        for (int i = 0; i < 4; i++)
#pragma unroll
            for (int j = 0; j < 48; j++) asm volatile("" : "=r"(rp[i][j]));
        acc_init(acc);
    }
    static_phase(tm, cta, acc, rp);
    float s[4] = {0.f, 0.f, 0.f, 0.f};
#pragma unroll 1
    for (int phv = 0;; phv = 1) {
        const int ph = __shfl_sync(0xffffffffu, phv, 0);
        attention_pass(tm, p, cta, ph, tag0, acc, rp, s);
        if (ph) break;
        uint32_t rx[32];
        {
            UVARS
            load_kfrag(rx, k_offset(slots, wj, tid_now() & 31));
            wg_bar_or(barid, false);
            if (worker && wj == 3) tma_rows(&tm.wo, cta * 32 + wg * 16, slots, SM_WBAR);
            if (cta < 112) mbar_wait(SM_DBAR, 0);
        }
        if (worker) gemv_chain<false>(tm, p, cta, tag0 + 1);
        UVARS
        const int lane = tid_now() & 31;
        const uint4* src = &g_s.q[1][cta >> 7][head][wj * 32 + lane];
        uint4 v;
        uint32_t it = 0;
        do {
            spin_guard(it);
            if (it == 1 || !worker) delay_cycles(D_AG);
            v = ll_ld(src);
            if (it == 1 && wj == 1) tma_tile(&tm.k, tb + T_DYN0 + ui, slots, bars);
        } while (__any_sync(0xffffffffu, v.y != tag0 + 1 || v.w != tag0 + 1));
        sts64(qbase + (wj * 32 + lane) * 8, v.x, v.z);
        wg_bar_or(barid, false);
        TS(10);
        float s2[4] = {0.f, 0.f, 0.f, 0.f};
        s[0] = s[1] = s[2] = s[3] = 0.f;
        qk_half(s, s2, rx, Q_RD);
        qk_half(s, s2, rx + 16, Q_RD + 512);
#pragma unroll
        for (int i = 0; i < 4; i++) s[i] += s2[i];
        {
            Pack pk = {SM_CMP + wg * 16, SM_ESC + wg * (ECAP * 8), 0};
            const uint32_t store = slots + 2 * SLOT + (wj * 32 + lane) * 16, up = lds32(pk.cmp);
#pragma unroll 1
            for (int pv = 2; pv >= 0; pv--) {
                const int pos = __shfl_sync(0xffffffffu, pv, 0), c = (0x120 >> (4 * pos)) & 3;
                pk.key = c << 11 | wj << 5 | lane;
                const uint32_t flags = esc_flags(pk);
                float z[4] = {0.f, 0.f, 0.f, 0.f}, z2[4] = {0.f, 0.f, 0.f, 0.f};
#pragma unroll 1
                for (int h = 0; h < 2; h++) {
                    uint32_t a[16];
                    unpack16(a, up, store + pos * 12288 + h * 6144, h, flags, pk);
                    qk_half(z, z2, a, Q_RD + h * 512);
                }
                asm volatile("{\n.reg .pred p;\nsetp.eq.u32 p, %5, 0;\n@p st.shared.v4.f32 [%0], {%1,%2,%3,%4};\n}"
                             ::"r"(store + 32768 + (c >> 1) * 2048), "f"(z[0] + z2[0]), "f"(z[1] + z2[1]), "f"(z[2] + z2[2]),
                               "f"(z[3] + z2[3]), "r"(((lane >> 1) ^ c) & 1) : "memory");
                if (pos == 1) {
                    if (wj == 2) {
                        bar_sync(8 + wg, 128);
                        tma_tile(&tm.v, tb + T_DYN0 + ui, slots + 3 * SLOT, bars + 24);
                    } else {
                        bar_arrive(8 + wg, 128);
                    }
                    TS(13);
                }
                __syncwarp();
            }
        }
        acc_init(acc);
    }
    if (worker) {
        UVARS
        if (wj == 3) tma_rows(&tm.wo, cta * 32 + wg * 16, slots + 2 * SLOT, SM_TBAR);
        if (wj == 2 && cta < 112) load_ffn(tm, cta, wg, slots + 3 * SLOT);
        gemv_chain<true>(tm, p, cta, tag0 + 2);
    }
}

typedef CUresult (*EncodeFn)(CUtensorMap*, CUtensorMapDataType, cuuint32_t, void*, const cuuint64_t*, const cuuint64_t*,
                             const cuuint32_t*, const cuuint32_t*, CUtensorMapInterleave, CUtensorMapSwizzle,
                             CUtensorMapL2promotion, CUtensorMapFloatOOBfill);

void make_map(EncodeFn encode, CUtensorMap* m, void* base, int rank, const cuuint64_t* gd, const cuuint64_t* gs,
              const cuuint32_t* bx, CUtensorMapSwizzle sw) {
    const cuuint32_t es[3] = {1, 1, 1};
    encode(m, CU_TENSOR_MAP_DATA_TYPE_BFLOAT16, rank, base, gd, gs, bx, es, CU_TENSOR_MAP_INTERLEAVE_NONE, sw,
           CU_TENSOR_MAP_L2_PROMOTION_NONE, CU_TENSOR_MAP_FLOAT_OOB_FILL_NONE);
}

}

extern "C" void kernel_launch(void* const* d_in, const int* in_sizes, int n_in, void* d_out, int out_size) {
    (void)in_sizes; (void)n_in; (void)out_size;
    static EncodeFn encode = nullptr;
    static void* scratch = nullptr;
    if (!encode) {
        void* fn = nullptr;
        cudaDriverEntryPointQueryResult qr;
        cudaGetDriverEntryPoint("cuTensorMapEncodeTiled", &fn, cudaEnableDefault, &qr);
        encode = (EncodeFn)fn;
        cudaGetSymbolAddress(&scratch, g_scratch);
        cudaFuncSetAttribute(fused_kernel, cudaFuncAttributeMaxDynamicSharedMemorySize, SM_TOTAL);
    }
    Maps tm;
    {
        const cuuint64_t gd[3] = {64, 8ull * 65536ull, 2}, gs[2] = {256, 128};
        const cuuint32_t bx[3] = {64, 64, 2};
        make_map(encode, &tm.k, d_in[1], 3, gd, gs, bx, CU_TENSOR_MAP_SWIZZLE_128B);
        make_map(encode, &tm.v, d_in[2], 3, gd, gs, bx, CU_TENSOR_MAP_SWIZZLE_128B);
    }
    {
        const cuuint64_t gd[2] = {4096, 512}, gs[1] = {8192};
        const cuuint32_t bx[2] = {32, 256};
        make_map(encode, &tm.wq, d_in[3], 2, gd, gs, bx, CU_TENSOR_MAP_SWIZZLE_64B);
    }
    {
        const cuuint64_t gd[3] = {64, 4096, 8}, gs[2] = {1024, 128};
        const cuuint32_t bx[3] = {64, 16, 8};
        make_map(encode, &tm.wo, d_in[4], 3, gd, gs, bx, CU_TENSOR_MAP_SWIZZLE_128B);
        const cuuint64_t gd2[3] = {64, 1792, 8};
        make_map(encode, &tm.wd, d_in[8], 3, gd2, gs, bx, CU_TENSOR_MAP_SWIZZLE_128B);
    }
    {
        const cuuint64_t gd[2] = {1792, 512}, gs[1] = {3584};
        const cuuint32_t bx[2] = {16, 256};
        make_map(encode, &tm.wg, d_in[6], 2, gd, gs, bx, CU_TENSOR_MAP_SWIZZLE_32B);
        make_map(encode, &tm.wu, d_in[7], 2, gd, gs, bx, CU_TENSOR_MAP_SWIZZLE_32B);
    }
    Params p;
    p.x = (const __nv_bfloat16*)d_in[0];
    p.k = (const char*)d_in[1];
    p.v = (const char*)d_in[2];
    p.wq = (const char*)d_in[3];
    p.wo = (const char*)d_in[4];
    p.wg = (const char*)d_in[6];
    p.wu = (const char*)d_in[7];
    p.wd = (const char*)d_in[8];
    p.out = (__nv_bfloat16*)d_out;
    p.s = (Scratch*)scratch;
    fused_kernel<<<NCTA, 256, SM_TOTAL, cudaStreamPerThread>>>(tm, p);
}
```

```cpp
#include <cuda_runtime.h>
#include <cuda_bf16.h>
#include <cuda.h>
#include <stdint.h>

namespace {

constexpr int NCTA      = 132;
constexpr int NUNIT     = 33;
constexpr int NTILE     = 1024;
constexpr int SLOT      = 16384;
constexpr int NSTAT     = 7;
constexpr int T_DYN0    = NSTAT * NUNIT;
constexpr int T_KEEP0   = NTILE - 200;
constexpr int T_KEEPEND = NTILE - 33;
constexpr int KEEPCAP   = 32;
constexpr int ECAP      = 28;
constexpr int D_AR      = 650;
constexpr int D_SKIP    = 1500;
constexpr int D_AG      = 100;
constexpr int D_KV      = 300;
constexpr unsigned SPIN_LIMIT = 1u << 22;

constexpr uint32_t SM_BASE  = 1024;
constexpr uint32_t USTR     = 2 * SLOT + 3 * 24576;
constexpr uint32_t SM_SLOTS = SM_BASE;
constexpr uint32_t SM_WG    = SM_SLOTS + 2 * USTR;
constexpr uint32_t SM_Q     = SM_WG + SLOT;
constexpr uint32_t SM_P     = SM_Q + 1024;
constexpr uint32_t SM_RED   = SM_P + 1024;
constexpr uint32_t SM_MX    = SM_RED;
constexpr uint32_t SM_BAR   = SM_RED + 192;
constexpr uint32_t SM_WBAR  = SM_BAR + 96;
constexpr uint32_t SM_TBAR  = SM_BAR + 104;
constexpr uint32_t SM_DBAR  = SM_BAR + 112;
constexpr uint32_t SM_KEEP  = SM_BAR + 128;
constexpr uint32_t SM_ST    = SM_KEEP + 128;
constexpr uint32_t SM_CMP   = SM_ST + 32;
constexpr uint32_t SM_ESC   = SM_CMP + 32;
constexpr int SM_TOTAL      = SM_ESC + 2 * ECAP * 8 - SM_BASE;
static_assert(SM_TOTAL <= 232448 && ECAP <= 32, "smem");

struct __align__(1024) Scratch {
    uint4 part[128][8][NUNIT][2];
    uint4 ar[4][2][128][8];
    uint2 x2[256];
    uint4 q[2][2][8][128];
    unsigned ticket[2][8][32];
    unsigned done[32];
    unsigned epoch;
};
__device__ Scratch g_scratch;
#define g_s (*p.s)

struct Maps { CUtensorMap k, v, wq, wo, wg, wu, wd; };
struct Params {
    const __nv_bfloat16* x;
    const char* k;
    const char* v;
    const char* wq;
    const char* wo;
    const char* wg;
    const char* wu;
    const char* wd;
    __nv_bfloat16* out;
    Scratch* s;
};

__device__ __forceinline__ void mbar_init(uint32_t bar, uint32_t cnt) {
    asm volatile("{\n.reg .pred p;\nelect.sync _|p, 0xffffffff;\n@p mbarrier.init.shared::cta.b64 [%0], %1;\n}" ::"r"(bar), "r"(cnt) : "memory");
}
__device__ __forceinline__ void mbar_wait(uint32_t bar, uint32_t parity) {
    asm volatile("{\n.reg .pred p, q;\n.reg .u32 c;\nmov.u32 c, 0;\n"
                 "W_%=:\nmbarrier.try_wait.parity.shared::cta.b64 p, [%0], %1;\nvote.sync.all.pred p, p, 0xffffffff;\n"
                 "@p bra.uni D_%=;\nadd.u32 c, c, 1;\nsetp.lt.u32 q, c, %2;\n@q bra.uni W_%=;\ntrap;\nD_%=:\n}"
                 ::"r"(bar), "r"(parity), "n"(SPIN_LIMIT) : "memory");
}
__device__ __forceinline__ void spin_guard(uint32_t& it) {
    asm volatile("{\n.reg .pred q;\nadd.u32 %0, %0, 1;\nsetp.gt.u32 q, %0, %1;\n@q trap;\n}" : "+r"(it) : "n"(SPIN_LIMIT));
}
constexpr uint64_t POL_FIRST = 0x12f0000000000000ull, POL_NORMAL = 0x16f0000000000000ull;
__device__ __forceinline__ void tma_rows(const CUtensorMap* tm, int row, uint32_t dst, uint32_t bar) {
    asm volatile("{\n.reg .pred p;\nelect.sync _|p, 0xffffffff;\n"
                 "@p mbarrier.arrive.expect_tx.shared::cta.b64 _, [%4], %6;\n"
                 "@p cp.async.bulk.tensor.3d.shared::cluster.global.mbarrier::complete_tx::bytes.L2::cache_hint "
                 "[%0], [%1, {%2, %3, %2}], [%4], %5;\n}"
                 ::"r"(dst), "l"(tm), "r"(0), "r"(row), "r"(bar), "l"(POL_FIRST), "r"(SLOT) : "memory");
}
__device__ __forceinline__ void tma_tile(const CUtensorMap* tm, int gtile, uint32_t dst, uint32_t bar) {
    tma_rows(tm, gtile * 64, dst, bar);
}
__device__ __forceinline__ void expect_tx(uint32_t bar, uint32_t bytes) {
    asm volatile("{\n.reg .pred p;\nelect.sync _|p, 0xffffffff;\n@p mbarrier.arrive.expect_tx.shared::cta.b64 _, [%0], %1;\n}"
                 ::"r"(bar), "r"(bytes) : "memory");
}
__device__ __forceinline__ void tma_2d(const CUtensorMap* tm, int c0, int c1, uint32_t dst, uint32_t bar) {
    asm volatile("{\n.reg .pred p;\nelect.sync _|p, 0xffffffff;\n"
                 "@p cp.async.bulk.tensor.2d.shared::cluster.global.mbarrier::complete_tx::bytes.L2::cache_hint "
                 "[%0], [%1, {%2, %3}], [%4], %5;\n}"
                 ::"r"(dst), "l"(tm), "r"(c0), "r"(c1), "r"(bar), "l"(POL_FIRST) : "memory");
}
__device__ __forceinline__ void l2_prefetch(const void* p, uint32_t bytes, uint64_t pol) {
    asm volatile("{\n.reg .pred p;\nelect.sync _|p, 0xffffffff;\n"
                 "@p cp.async.bulk.prefetch.L2.global.L2::cache_hint [%0], %1, %2;\n}" ::"l"(p), "r"(bytes), "l"(pol) : "memory");
}
__device__ __forceinline__ void ldsm4(uint32_t* r, uint32_t a) {
    asm volatile("ldmatrix.sync.aligned.m8n8.x4.shared.b16 {%0,%1,%2,%3}, [%4];"
                 : "=r"(r[0]), "=r"(r[1]), "=r"(r[2]), "=r"(r[3]) : "r"(a) : "memory");
}
__device__ __forceinline__ void ldsm4t(uint32_t* r, uint32_t a) {
    asm volatile("ldmatrix.sync.aligned.m8n8.x4.trans.shared.b16 {%0,%1,%2,%3}, [%4];"
                 : "=r"(r[0]), "=r"(r[1]), "=r"(r[2]), "=r"(r[3]) : "r"(a) : "memory");
}
__device__ __forceinline__ void mma(float* c, const uint32_t* a, uint32_t b0, uint32_t b1) {
    asm volatile("mma.sync.aligned.m16n8k16.row.col.f32.bf16.bf16.f32 {%0,%1,%2,%3}, {%4,%5,%6,%7}, {%8,%9}, {%0,%1,%2,%3};"
                 : "+f"(c[0]), "+f"(c[1]), "+f"(c[2]), "+f"(c[3])
                 : "r"(a[0]), "r"(a[1]), "r"(a[2]), "r"(a[3]), "r"(b0), "r"(b1));
}
__device__ __forceinline__ uint32_t movm(uint32_t a) {
    uint32_t d; asm volatile("movmatrix.sync.aligned.m8n8.trans.b16 %0, %1;" : "=r"(d) : "r"(a)); return d;
}
__device__ __forceinline__ uint32_t pack_bf16(float lo, float hi) {
    uint32_t d; asm("cvt.rn.bf16x2.f32 %0, %1, %2;" : "=r"(d) : "f"(hi), "f"(lo)); return d;
}
__device__ __forceinline__ float bf16r(float v) { return __uint_as_float(pack_bf16(v, 0.f) << 16); }
__device__ __forceinline__ float bf_lo(uint32_t w) { return __uint_as_float(w << 16); }
__device__ __forceinline__ float bf_hi(uint32_t w) { return __uint_as_float(w & 0xffff0000u); }
__device__ __forceinline__ float ex2(float v) { float d; asm("ex2.approx.ftz.f32 %0, %1;" : "=f"(d) : "f"(v)); return d; }
__device__ __forceinline__ uint4 lds128(uint32_t a) {
    uint4 v; asm volatile("ld.shared.v4.u32 {%0,%1,%2,%3}, [%4];" : "=r"(v.x), "=r"(v.y), "=r"(v.z), "=r"(v.w) : "r"(a) : "memory"); return v;
}
__device__ __forceinline__ uint2 lds64(uint32_t a) {
    uint2 v; asm volatile("ld.shared.v2.u32 {%0,%1}, [%2];" : "=r"(v.x), "=r"(v.y) : "r"(a) : "memory"); return v;
}
__device__ __forceinline__ uint32_t lds32(uint32_t a) {
    uint32_t v; asm volatile("ld.shared.u32 %0, [%1];" : "=r"(v) : "r"(a) : "memory"); return v;
}
__device__ __forceinline__ void sts128(uint32_t a, uint32_t x, uint32_t y, uint32_t z, uint32_t w) {
    asm volatile("st.shared.v4.u32 [%0], {%1,%2,%3,%4};" ::"r"(a), "r"(x), "r"(y), "r"(z), "r"(w) : "memory");
}
__device__ __forceinline__ void sts64(uint32_t a, uint32_t x, uint32_t y) {
    asm volatile("st.shared.v2.u32 [%0], {%1,%2};" ::"r"(a), "r"(x), "r"(y) : "memory");
}
__device__ __forceinline__ void sts32(uint32_t a, uint32_t x) {
    asm volatile("st.shared.u32 [%0], %1;" ::"r"(a), "r"(x) : "memory");
}
__device__ __forceinline__ void sts16(uint32_t a, uint32_t x) {
    asm volatile("st.shared.u16 [%0], %1;" ::"r"(a), "h"((unsigned short)x) : "memory");
}
__device__ __forceinline__ uint32_t lds16(uint32_t a) {
    unsigned short v; asm volatile("ld.shared.u16 %0, [%1];" : "=h"(v) : "r"(a) : "memory"); return v;
}
__device__ __forceinline__ bool wg_bar_or(int id, bool p) {
    uint32_t r;
    asm volatile("{\n.reg .pred a, b;\nsetp.ne.u32 a, %2, 0;\nbar.red.or.pred b, %1, 128, a;\nselp.u32 %0, 1, 0, b;\n}"
                 : "=r"(r) : "r"(id), "r"((uint32_t)p) : "memory");
    return r != 0;
}
__device__ __forceinline__ uint4 ll_ld(const uint4* p) {
    unsigned long long a, b;
    asm volatile("ld.relaxed.gpu.global.v2.b64 {%0,%1}, [%2];" : "=l"(a), "=l"(b) : "l"(p) : "memory");
    return make_uint4((uint32_t)a, (uint32_t)(a >> 32), (uint32_t)b, (uint32_t)(b >> 32));
}
__device__ __forceinline__ void ll_st(uint4* p, uint32_t v0, uint32_t t0, uint32_t v1, uint32_t t1) {
    unsigned long long a = ((unsigned long long)t0 << 32) | v0, b = ((unsigned long long)t1 << 32) | v1;
    asm volatile("st.relaxed.gpu.global.v2.b64 [%0], {%1,%2};" ::"l"(p), "l"(a), "l"(b) : "memory");
}
__device__ __forceinline__ uint4 ll_ld_last(const uint4* p) {
    unsigned long long a, b;
    asm volatile("ld.relaxed.gpu.global.L2::cache_hint.v2.b64 {%0,%1}, [%2], %3;" : "=l"(a), "=l"(b) : "l"(p), "l"(POL_FIRST) : "memory");
    return make_uint4((uint32_t)a, (uint32_t)(a >> 32), (uint32_t)b, (uint32_t)(b >> 32));
}
__device__ __forceinline__ void bar_sync(int id, int n) { asm volatile("bar.sync %0, %1;" ::"r"(id), "r"(n) : "memory"); }
__device__ __forceinline__ void bar_arrive(int id, int n) { asm volatile("bar.arrive %0, %1;" ::"r"(id), "r"(n) : "memory"); }
__device__ __forceinline__ void delay_cycles(int n) {
    if (n > 0) {
        uint32_t t0, t1;
        asm volatile("mov.u32 %0, %%clock;" : "=r"(t0));
        do { asm volatile("mov.u32 %0, %%clock;" : "=r"(t1)); } while (t1 - t0 < (uint32_t)n);
    }
}
__device__ __forceinline__ int tid_now() {
    int t; asm volatile("mov.u32 %0, %%tid.x;" : "=r"(t)); return t;
}
__device__ __forceinline__ bool mbar_test(uint32_t bar, uint32_t parity) {
    uint32_t ok;
    asm volatile("{\n.reg .pred p;\nmbarrier.test_wait.parity.shared::cta.b64 p, [%1], %2;\nselp.u32 %0, 1, 0, p;\n}"
                 : "=r"(ok) : "r"(bar), "r"(parity) : "memory");
    return ok != 0;
}

struct Acc {
    float o[2][4];
    float l[4];
    float m0, m1;
};

constexpr float SCALE_LOG2 = 0.08838834764831845f * 1.4426950408889634f;

__device__ __forceinline__ void softmax_step(float* s, Acc& a, uint32_t p_wr, uint32_t mx, int barid, int lane, int wj) {
#pragma unroll
    for (int i = 0; i < 4; i++) s[i] *= SCALE_LOG2;
    bool over = fmaxf(s[0], s[2]) > a.m0 || fmaxf(s[1], s[3]) > a.m1;
    {
        uint32_t b0 = movm(pack_bf16(ex2(s[0] - a.m0), ex2(s[1] - a.m1)));
        uint32_t b1 = movm(pack_bf16(ex2(s[2] - a.m0), ex2(s[3] - a.m1)));
        if (lane < 16) sts64(p_wr, b0, b1);
    }
    if (wg_bar_or(barid, over)) {
        float x0 = fmaxf(s[0], s[2]), x1 = fmaxf(s[1], s[3]);
#pragma unroll
        for (int d = 4; d < 32; d <<= 1) {
            x0 = fmaxf(x0, __shfl_xor_sync(0xffffffffu, x0, d));
            x1 = fmaxf(x1, __shfl_xor_sync(0xffffffffu, x1, d));
        }
        if (lane < 2) sts64(mx + wj * 16 + lane * 8, __float_as_uint(x0), __float_as_uint(x1));
        wg_bar_or(barid, false);
        float n0 = a.m0, n1 = a.m1;
#pragma unroll
        for (int j = 0; j < 4; j++) {
            uint2 v = lds64(mx + j * 16 + (lane & 1) * 8);
            n0 = fmaxf(n0, __uint_as_float(v.x));
            n1 = fmaxf(n1, __uint_as_float(v.y));
        }
        float f0 = ex2(a.m0 - n0), f1 = ex2(a.m1 - n1);
        a.m0 = n0; a.m1 = n1;
        a.o[0][0] *= f0; a.o[0][2] *= f0; a.o[1][0] *= f0; a.o[1][2] *= f0; a.l[0] *= f0; a.l[2] *= f0;
        a.o[0][1] *= f1; a.o[0][3] *= f1; a.o[1][1] *= f1; a.o[1][3] *= f1; a.l[1] *= f1; a.l[3] *= f1;
        uint32_t b0 = movm(pack_bf16(ex2(s[0] - n0), ex2(s[1] - n1)));
        uint32_t b1 = movm(pack_bf16(ex2(s[2] - n0), ex2(s[3] - n1)));
        if (lane < 16) sts64(p_wr, b0, b1);
        wg_bar_or(barid, false);
    }
}

__device__ __forceinline__ uint32_t mul2(uint32_t a, uint32_t b) {
    uint32_t d; asm("mul.rn.bf16x2 %0, %1, %2;" : "=r"(d) : "r"(a), "r"(b)); return d;
}
struct Pack {
    uint32_t cmp;
    uint32_t esc;
    uint32_t key;
};
__device__ __forceinline__ void pack16(const uint32_t* a, uint32_t up, uint32_t d0, uint32_t d1, uint32_t d2, int it,
                                       const Pack& pk) {
    const uint32_t dn = 0x7f007f00u - up;
    uint32_t l[8], n[4], bad = 0;
#pragma unroll
    for (int g = 0; g < 4; g++) {
        uint32_t z[4], e = 0;
#pragma unroll
        for (int j = 0; j < 4; j++) {
            z[j] = mul2(a[4 * g + j], dn);
            e |= mul2(z[j], up) ^ a[4 * g + j];
        }
        const uint32_t x0 = __byte_perm(z[0], z[1], 0x7531), x1 = __byte_perm(z[2], z[3], 0x7531);
        l[2 * g] = __byte_perm(z[0], z[1], 0x6420);
        l[2 * g + 1] = __byte_perm(z[2], z[3], 0x6420);
        n[g] = x0 | __funnelshift_l(x1, x1, 4);
        if (e | ((x0 | x1) & 0x78787878u)) bad |= 1u << g;
        if (g & 1) sts128(g == 1 ? d0 : d1, l[2 * g - 2], l[2 * g - 1], l[2 * g], l[2 * g + 1]);
    }
    sts128(d2, n[0], n[1], n[2], n[3]);
    if (bad) {
        uint32_t i;
        asm volatile("atom.shared.add.u32 %0, [%1], %2;" : "=r"(i) : "r"(pk.cmp + 8 + (d2 >> 31)), "r"(__popc(bad)) : "memory");
#pragma unroll
        for (int g = 0; g < 4; g++) {
            asm volatile("{\n.reg .pred p, q;\n.reg .u32 a;\nsetp.ne.u32 p, %1, 0;\nsetp.lt.and.u32 q, %0, %5, p;\n"
                         "@p st.shared.v2.u32 [%6], {%7, %8};\n@p st.shared.u32 [%9], %10;\nmad.lo.u32 a, %0, 8, %2;\n"
                         "@q st.shared.v2.u32 [a], {%3, %4};\n@p add.u32 %0, %0, 1;\n}"
                         : "+r"(i)
                         : "r"(bad & (1u << g)), "r"(pk.esc), "r"(pk.key | it << 9 | g << 7), "r"(a[4 * g + 3]),
                           "n"(ECAP), "r"((g < 2 ? d0 : d1) + (g & 1) * 8), "r"(a[4 * g]), "r"(a[4 * g + 1]), "r"(d2 + g * 4),
                           "r"(a[4 * g + 2]) : "memory");
        }
    }
    __syncwarp();
}
__device__ __forceinline__ uint32_t esc_flags(const Pack& pk) {
    const uint32_t e = lds32(pk.esc + min(pk.key & 31u, ECAP - 1u) * 8);
    return __reduce_or_sync(0xffffffffu, ((e ^ pk.key) & ~0x3f9fu) == 0 ? 1u << ((e >> 9) & 31) : 0u);
}
__device__ __forceinline__ void unpack16(uint32_t* a, uint32_t up, uint32_t c, int it, uint32_t flags, const Pack& pk) {
    const uint4 nn = lds128(c + 4096);
    const uint4 l0 = lds128(c), l1 = lds128(c + 2048);
    const uint32_t n[4] = {nn.x, nn.y, nn.z, nn.w};
    const uint32_t l[8] = {l0.x, l0.y, l0.z, l0.w, l1.x, l1.y, l1.z, l1.w};
#pragma unroll
    for (int g = 0; g < 4; g++) {
        const uint32_t h0 = n[g] & 0x87878787u, h1 = __funnelshift_r(n[g], n[g], 4) & 0x87878787u;
        a[4 * g]     = mul2(__byte_perm(l[2 * g], h0, 0x5140), up);
        a[4 * g + 1] = mul2(__byte_perm(l[2 * g], h0, 0x7362), up);
        a[4 * g + 2] = mul2(__byte_perm(l[2 * g + 1], h1, 0x5140), up);
        a[4 * g + 3] = mul2(__byte_perm(l[2 * g + 1], h1, 0x7362), up);
    }
    if (flags >> it & 1) {
        const uint32_t me = pk.key | it << 9;
        const uint2 e = lds64(pk.esc + min(me & 31u, ECAP - 1u) * 8);
        uint32_t hit = __ballot_sync(0xffffffffu, ((e.x ^ me) & ~0x19fu) == 0) & (uint32_t)((1ull << ECAP) - 1);
#pragma unroll 1
        while (hit) {
            const int src = __ffs(hit) - 1;
            hit &= hit - 1;
            const uint32_t d = __shfl_sync(0xffffffffu, e.x, src) ^ me, v = __shfl_sync(0xffffffffu, e.y, src);
#pragma unroll
            for (int g = 0; g < 4; g++)
                asm volatile("{\n.reg .pred p;\nsetp.eq.u32 p, %4, %5;\n@p ld.shared.v2.u32 {%0, %1}, [%6];\n"
                             "@p ld.shared.u32 %2, [%7];\n@p mov.u32 %3, %8;\n}"
                             : "+r"(a[4 * g]), "+r"(a[4 * g + 1]), "+r"(a[4 * g + 2]), "+r"(a[4 * g + 3])
                             : "r"(d), "n"(g << 7), "r"(c + (g >> 1) * 2048 + (g & 1) * 8), "r"(c + 4096 + g * 4), "r"(v) : "memory");
        }
    }
}

__device__ __forceinline__ void qk_half(float* s, float* s2, const uint32_t* a, uint32_t q) {
    const uint4 q0 = lds128(q), q1 = lds128(q + 256);
    mma(s, a, q0.x, q0.y);
    mma(s2, a + 4, q0.z, q0.w);
    mma(s, a + 8, q1.x, q1.y);
    mma(s2, a + 12, q1.z, q1.w);
}
__device__ __forceinline__ void mma_ones(float* c, uint32_t b) {
    asm volatile("mma.sync.aligned.m16n8k8.row.col.f32.bf16.bf16.f32 {%0,%1,%2,%3}, {%4,%4}, {%5}, {%0,%1,%2,%3};"
                 : "+f"(c[0]), "+f"(c[1]), "+f"(c[2]), "+f"(c[3]) : "r"(0x3f803f80u), "r"(b));
}
template <bool SMALL>
__device__ __forceinline__ void pv_half(Acc& a, const uint32_t* f, uint32_t pa) {
    const uint32_t ones[4] = {0x3f803f80u, 0x3f803f80u, 0x3f803f80u, 0x3f803f80u};
    const uint4 pp = lds128(pa);
    mma(a.o[0], f, pp.x, pp.y);
    mma(a.o[1], f + 4, pp.x, pp.y);
    if (SMALL) { mma_ones(a.l, pp.x); mma_ones(a.l, pp.y); } else mma(a.l, ones, pp.x, pp.y);
    mma(a.o[0], f + 8, pp.z, pp.w);
    mma(a.o[1], f + 12, pp.z, pp.w);
    if (SMALL) { mma_ones(a.l, pp.z); mma_ones(a.l, pp.w); } else mma(a.l, ones, pp.z, pp.w);
}
__device__ __forceinline__ void load_khalf(uint32_t* a, uint32_t k) {
#pragma unroll
    for (int j = 0; j < 4; j++) ldsm4(a + j * 4, k ^ (j << 5));
    __syncwarp();
}
__device__ __forceinline__ void load_vhalf(uint32_t* f, uint32_t v) {
    ldsm4t(f, v);
    ldsm4t(f + 4, v ^ 32);
    ldsm4t(f + 8, v + 2048);
    ldsm4t(f + 12, (v ^ 32) + 2048);
    __syncwarp();
}
__device__ __forceinline__ void park(uint32_t* r, uint32_t kb, uint32_t vb) {
#pragma unroll
    for (int j = 0; j < 12; j++) {
        const int it = j / 3, c = j % 3;
        const uint32_t ad = it < 2 ? (kb ^ (c << 5)) + it * 8192 : (vb ^ ((c & 1) << 5)) + (c >> 1) * 2048 + (it - 2) * 4096;
        const uint4 u = lds128(ad);
        r[4 * j] = u.x; r[4 * j + 1] = u.y; r[4 * j + 2] = u.z; r[4 * j + 3] = u.w;
    }
}
__device__ __forceinline__ void unpark(const uint32_t* r, uint32_t c) {
#pragma unroll
    for (int j = 0; j < 12; j++) sts128(c + j * 2048, r[4 * j], r[4 * j + 1], r[4 * j + 2], r[4 * j + 3]);
}
__device__ __forceinline__ uint32_t k_offset(uint32_t slots, int wj, int lane) {
    const int row = wj * 16 + (lane & 7) + ((lane >> 3) & 1) * 8;
    return slots + row * 128 + (((lane >> 4) ^ (row & 7)) << 4);
}
__device__ __forceinline__ uint32_t v_offset(uint32_t slots, int wj, int lane) {
    const int key = (lane & 7) + (lane >> 4) * 8, cg = wj * 4 + ((lane >> 3) & 1);
    return slots + (cg >> 3) * 8192 + key * 128 + (((cg & 7) ^ (key & 7)) << 4);
}
__device__ __forceinline__ void load_kfrag(uint32_t* rk, uint32_t kb) {
#pragma unroll
    for (int ks = 0; ks < 8; ks++) ldsm4(rk + ks * 4, (kb ^ ((ks & 3) << 5)) + (ks >> 2) * 8192);
}

template <int NPRE>
__device__ __forceinline__ void ln_gemv_part(uint32_t (*f)[8], uint32_t a0, uint32_t a1, uint32_t kstride, uint32_t xw,
                                             int wq, int lane) {
    const int t = lane & 3, g = lane >> 2;
    float c0[4] = {0.f, 0.f, 0.f, 0.f}, c1[4] = {0.f, 0.f, 0.f, 0.f};
#pragma unroll
    for (int ks = 0; ks < 4; ks++) {
        uint32_t* ff = f[ks % NPRE];
        if (ks >= NPRE) {
            ldsm4t(ff, a0 + ks * kstride);
            ldsm4t(ff + 4, a1 + ks * kstride);
        }
        uint32_t xa = __shfl_sync(0xffffffffu, xw, ks * 8 + t), xb = __shfl_sync(0xffffffffu, xw, ks * 8 + 4 + t);
        if (g & 1) xa = xb = 0x3f803f80u;
        mma(c0, ff, xa, xb);
        mma(c1, ff + 4, xa, xb);
    }
    {
        const float a = bf_lo(xw), b = bf_hi(xw);
        const float su = a + b, sq = fmaf(a, a, b * b);
        float keep = (lane & 16) ? sq : su, send = (lane & 16) ? su : sq;
        keep += __shfl_xor_sync(0xffffffffu, send, 16);
#pragma unroll
        for (int k = 8; k > 0; k >>= 1) keep += __shfl_xor_sync(0xffffffffu, keep, k);
        if ((lane & 15) == 0) sts32(SM_RED + (lane >> 4) * 32 + wq * 4, __float_as_uint(keep));
    }
    float y = (t & 2) ? ((t & 1) ? c1[2] : c1[0]) : ((t & 1) ? c0[2] : c0[0]);
    float z = (t & 2) ? ((t & 1) ? c1[3] : c1[1]) : ((t & 1) ? c0[3] : c0[1]);
    sts64(SM_Q + wq * 256 + (t * 8 + g) * 8, __float_as_uint(y), __float_as_uint(z));
}
__device__ __forceinline__ float sum4(uint4 u) {
    return (__uint_as_float(u.x) + __uint_as_float(u.y)) + (__uint_as_float(u.z) + __uint_as_float(u.w));
}
__device__ __forceinline__ float ln_gemv_fin(int lane) {
    float mean, rstd;
    {
        const uint4 a = lds128(SM_RED), b = lds128(SM_RED + 16), c = lds128(SM_RED + 32), d = lds128(SM_RED + 48);
        mean = (sum4(a) + sum4(b)) * (1.f / 512.f);
        const float var = fmaxf(fmaf(sum4(c) + sum4(d), 1.f / 512.f, -mean * mean), 0.f) + 1e-5f;
        asm("rsqrt.approx.ftz.f32 %0, %1;" : "=f"(rstd) : "f"(var));
    }
    uint2 u[8];
#pragma unroll
    for (int j = 0; j < 8; j++) u[j] = lds64(SM_Q + j * 256 + lane * 8);
#define S8(f) (((__uint_as_float(u[0].f) + __uint_as_float(u[1].f)) + (__uint_as_float(u[2].f) + __uint_as_float(u[3].f))) + \
               ((__uint_as_float(u[4].f) + __uint_as_float(u[5].f)) + (__uint_as_float(u[6].f) + __uint_as_float(u[7].f))))
    return (S8(x) - mean * S8(y)) * rstd;
#undef S8
}
__device__ __forceinline__ void ar_add(uint4* dst, float y0, float y1) {
    asm volatile("red.relaxed.gpu.global.add.v4.f32 [%0], {%1, %2, %3, %1};" ::"l"(dst), "f"(1.f), "f"(y0), "f"(y1) : "memory");
}

__device__ __forceinline__ int unit_head(int cta, int wg) { return cta < 128 ? ((cta + (cta >> 3)) & 7) : (cta - 128) * 2 + wg; }
__device__ __forceinline__ int unit_index(int cta, int wg) { return cta < 128 ? (cta >> 3) * 2 + wg : 32; }
__device__ __forceinline__ void issue_item(int j, const Maps& tm, int tb, int ui, uint32_t slots, uint32_t bars) {
    const int slot = (int)((0x1010210432105432ull >> (4 * j)) & 15);
    tma_tile((j & 1) ? &tm.v : &tm.k, tb + (j >> 1) * NUNIT + ui, slots + slot * SLOT, bars + slot * 8);
}
__device__ __forceinline__ void load_ffn(const Maps& tm, int cta, int h, uint32_t z) {
    if (h) {
        tma_rows(&tm.wd, cta * 16, z, SM_WBAR);
    } else {
        expect_tx(SM_WBAR, SLOT);
        tma_2d(&tm.wu, cta * 16, 0, z, SM_WBAR);
        tma_2d(&tm.wu, cta * 16, 256, z + 8192, SM_WBAR);
    }
}
__device__ __forceinline__ void load_wq(const Maps& tm, int cta, int h, uint32_t z) {
    expect_tx(SM_WBAR, SLOT);
    tma_2d(&tm.wq, cta * 32, h * 256, z, SM_WBAR);
}
__device__ __forceinline__ void draw_ticket(uint32_t& ticket, const Params& p, int ph, int head, int lane) {
    asm volatile("{\n.reg .pred p;\nsetp.eq.u32 p, %2, 0;\n@p atom.relaxed.gpu.global.inc.u32 %0, [%1], 0xfffffffe;\n}"
                 : "+r"(ticket) : "l"(&g_s.ticket[ph][head][0]), "r"(lane) : "memory");
}
#define DESC(sk, sv) ((uint32_t)((sk) | ((sv) << 3) | 64))

__device__ __forceinline__ uint4* part_dst(const Params& p, int head, int ui, int tid) {
    const int lane = tid & 31, g = lane >> 2, t = lane & 3;
    return &g_s.part[(head * 4 + 2 * (t & 1) + (t >> 1)) * 4 + ((tid >> 5) & 3)][g >> 1][ui][g & 1];
}
__device__ __forceinline__ uint4* q_dst(const Params& p, int layer, int cta, int lane) {
    return &g_s.q[layer][(lane >> 3) & 1][cta >> 4][((cta & 3) * 16 + ((cta >> 2) & 3) * 4) * 2 + (lane & 7)];
}
__device__ __forceinline__ void publish_q(uint4* out, float r, uint32_t tag, int lane) {
    const int src = (lane & 1) * 16 + ((lane >> 1) & 3) * 2;
    const float q0 = __shfl_sync(0xffffffffu, r, src), q1 = __shfl_sync(0xffffffffu, r, src + 1);
    const float q2 = __shfl_sync(0xffffffffu, r, src + 8), q3 = __shfl_sync(0xffffffffu, r, src + 9);
    if (lane < 16) ll_st(out, pack_bf16(q0, q1), tag, pack_bf16(q2, q3), tag);
}

template <bool TAIL>
__device__ __forceinline__ void gemv_chain(const Maps& tm, const Params& p, const int cta, const uint32_t tag) {
    constexpr uint32_t Z_WO = SM_SLOTS + (TAIL ? 2 : 0) * SLOT, Z_GU = SM_SLOTS + (TAIL ? 3 : 0) * SLOT;
    const int wq = __shfl_sync(0xffffffffu, tid_now() >> 5, 0);
    uint32_t xo;
    {
        const int lane = tid_now() & 31, g = lane >> 2, t = lane & 3;
        if (!TAIL) {
            const unsigned short* xp = reinterpret_cast<const unsigned short*>(p.x) + wq * 64 + t * 16 + g;
            xo = xp[0] | (uint32_t)xp[8] << 16;
            if (wq == 0 && lane < 16) ll_st(q_dst(p, 1, cta, lane), 0, 0, 0, 0);
            __syncwarp();
            if (wq == 1) l2_prefetch(&g_s.ar[0][0][0][0] + (cta & 63) * 128, 2048, POL_NORMAL);
        } else {
            unsigned long long u;
            uint32_t it = 0;
            do {
                spin_guard(it);
                asm volatile("ld.relaxed.gpu.global.b64 %0, [%1];" : "=l"(u) : "l"(&g_s.x2[wq * 32 + lane]) : "memory");
            } while (__any_sync(0xffffffffu, (uint32_t)(u >> 32) != tag - 1));
            xo = (uint32_t)u;
        }
        const uint32_t t16 = tag & 0xffffu;
        const uint4* src = &g_s.part[cta][wq][lane & 15][lane >> 4];
        const bool three = (lane & 15) == 0;
        if (wq == 0) {
            const uint32_t target = ((tag >> 2) * 2 + (TAIL ? 2 : 1)) * (2 * NCTA);
            uint32_t it = 0;
            while (true) {
                uint32_t v;
                asm volatile("ld.acquire.gpu.global.u32 %0, [%1];" : "=r"(v) : "l"(&g_s.done[0]) : "memory");
                const int rem = __shfl_sync(0xffffffffu, (int)(target - v), 0);
                if (rem <= 0) break;
                spin_guard(it);
                if (rem > 16) delay_cycles(400);
            }
        }
        __syncthreads();
        uint4 a = ll_ld_last(src), b = ll_ld_last(src + 32), e = make_uint4(0, 0xff800000u | t16, 0, t16);
        if (three) e = ll_ld_last(src + 64);
        const uint32_t wa0 = Z_WO + wq * 2048 + ((lane & 7) + (lane >> 4) * 8) * 128 + ((((lane >> 3) & 1) ^ (lane & 7)) << 4);
        uint32_t f0[4][4], f1[4][4];
        mbar_wait(TAIL ? SM_TBAR : SM_WBAR, TAIL ? 0 : 1);
        if (TAIL) {
#pragma unroll
            for (int mt = 0; mt < 4; mt++) {
                ldsm4t(f0[mt], wa0 ^ (mt << 5));
                ldsm4t(f1[mt], (wa0 ^ (mt << 5)) + USTR);
            }
        }
        {
            uint32_t it = 0;
            while (__any_sync(0xffffffffu, ((a.y ^ t16) | (a.w ^ t16) | (b.y ^ t16) | (b.w ^ t16) | (e.y ^ t16) | (e.w ^ t16)) << 16 != 0)) {
                spin_guard(it);
                a = ll_ld_last(src);
                b = ll_ld_last(src + 32);
                if (three) e = ll_ld_last(src + 64);
            }
        }
        if (!TAIL && wq >= 6) l2_prefetch((wq == 6 ? p.wu : p.wd) + (size_t)cta * 14336, 14336, POL_FIRST);
        const float la = __uint_as_float(__byte_perm(a.w, a.y, 0x7632)), lb = __uint_as_float(__byte_perm(b.w, b.y, 0x7632));
        const float le = __uint_as_float(__byte_perm(e.w, e.y, 0x7632));
        float mm;
        {
            int k = __float_as_int(fmaxf(fmaxf(la, lb), le));
            k ^= (k >> 31) & 0x7fffffff;
            k = __reduce_max_sync(0xffffffffu, k);
            k ^= (k >> 31) & 0x7fffffff;
            mm = __int_as_float(k);
        }
        const float wa = ex2(la - mm), wb = ex2(lb - mm), we = ex2(le - mm);
        const float v0 = fmaf(we, __uint_as_float(e.x), fmaf(wb, __uint_as_float(b.x), wa * __uint_as_float(a.x)));
        const float v1 = fmaf(we, __uint_as_float(e.z), fmaf(wb, __uint_as_float(b.z), wa * __uint_as_float(a.z)));
        float ws = wa + wb + we;
        float kk = (lane & 8) ? v1 : v0;
        kk += __shfl_xor_sync(0xffffffffu, (lane & 8) ? v0 : v1, 8);
        ws += __shfl_xor_sync(0xffffffffu, ws, 8);
        if (!TAIL) {
#pragma unroll
            for (int mt = 0; mt < 2; mt++) {
                ldsm4t(f0[mt], wa0 ^ (mt << 5));
                ldsm4t(f1[mt], (wa0 ^ (mt << 5)) + USTR);
            }
        }
#pragma unroll
        for (int k = 4; k > 0; k >>= 1) {
            kk += __shfl_xor_sync(0xffffffffu, kk, k);
            ws += __shfl_xor_sync(0xffffffffu, ws, k);
        }
        {
            float r; asm("rcp.approx.ftz.f32 %0, %1;" : "=f"(r) : "f"(ws));
            const uint32_t o = pack_bf16(kk * r, 0.f);
            if ((lane & 7) == 0) sts16(SM_RED + 128 + (wq & 3) * 16 + (wq >> 2) * 8 + ((lane >> 3) & 1) * 4 + (lane >> 4) * 2, o);
        }
        uint4* out = &g_s.ar[TAIL ? 2 : 0][cta & 1][wq * 16 + (lane >> 1)][lane & 1];
        __syncthreads();
        const uint4 ob = lds128(SM_RED + 128 + t * 16);
        float c0[4] = {0.f, 0.f, 0.f, 0.f}, c1[4] = {0.f, 0.f, 0.f, 0.f};
#pragma unroll
        for (int mt = 0; mt < 4; mt++) {
            constexpr int NP = TAIL ? 4 : 2;
            uint32_t* g0 = f0[mt % NP];
            uint32_t* g1 = f1[mt % NP];
            if (mt >= NP) {
                ldsm4t(g0, wa0 ^ (mt << 5));
                ldsm4t(g1, (wa0 ^ (mt << 5)) + USTR);
            }
            const bool mine = (g >> 1) == mt;
            mma(c0, g0, mine ? ob.x : 0u, mine ? ob.y : 0u);
            mma(c1, g1, mine ? ob.z : 0u, mine ? ob.w : 0u);
        }
        ar_add(out, c0[0] + c1[0], c0[2] + c1[2]);
        if (!TAIL) {
            if (wq == 4 || wq == 5) bar_sync(4, 256); else bar_arrive(4, 256);
        }
    }
#pragma unroll 1
    for (int hv = 0; hv < 2; hv++) {
        const int half = __shfl_sync(0xffffffffu, hv, 0);
        const bool ffn = cta < 112;
        if (TAIL && (half ? cta != 0 : !ffn)) break;
        uint32_t t0;
        asm volatile("mov.u32 %0, %%clock;" : "=r"(t0));
        const int lane = tid_now() & 31, g = lane >> 2, t = lane & 3;
        const bool qs = !TAIL && half;
        [[maybe_unused]] const int h = wq - 4;
        [[maybe_unused]] const uint32_t z = SM_SLOTS + h * USTR;
        if (!TAIL && (wq == 4 || wq == 5)) {
            if (!half) {
                if (ffn) load_ffn(tm, cta, h, z);
            } else if (!(ffn && h == 0)) {
                if (!ffn) delay_cycles(D_SKIP);
                load_wq(tm, cta, h, z);
            }
        }
        if (!TAIL && !half && wq >= 6) l2_prefetch(p.wq + (size_t)(cta + (wq - 6) * 128) * 16384, 16384, POL_FIRST);
        constexpr int NPRE = TAIL ? 4 : 2;
        uint32_t f[NPRE][8];
        const int row = (wq & 3) * 64 + (lane & 7) + (lane >> 4) * 8;
        const uint32_t a0 = qs ? SM_SLOTS + (wq >> 2) * USTR + row * 64 + ((((lane >> 3) & 1) ^ ((lane >> 1) & 3)) << 4)
                               : SM_WG + (wq >> 2) * 8192 + row * 32 + ((((lane >> 3) ^ (lane >> 2)) & 1) << 4);
        const uint32_t a1 = qs ? a0 ^ 32 : a0 - (SM_WG - Z_GU), kstride = qs ? 1024 : 512;
        {
            const uint4* src = &g_s.ar[(TAIL ? 2 : 0) + half][0][wq * 16 + (lane >> 1)][lane & 1];
            const uint32_t cnt = __float_as_uint(half ? 56.f : 64.f);
            if (TAIL && !half) {
                mbar_wait(SM_WBAR, 0);
#pragma unroll
                for (int ks = 0; ks < NPRE; ks++) {
                    ldsm4t(f[ks], a0 + ks * kstride);
                    ldsm4t(f[ks] + 4, a1 + ks * kstride);
                }
            }
            {
                const uint32_t d = (half && !ffn) ? D_AR + D_SKIP : D_AR;
                uint32_t t1;
                do { asm volatile("mov.u32 %0, %%clock;" : "=r"(t1)); } while (t1 - t0 < d);
            }
            uint4 u, v;
            uint32_t it = 0;
            do {
                spin_guard(it);
                u = ll_ld(src);
                v = ll_ld(src + 1024);
            } while (__any_sync(0xffffffffu, u.x != cnt || u.w != cnt || v.x != cnt || v.w != cnt));
            const uint32_t y = pack_bf16(__uint_as_float(u.y) + __uint_as_float(v.y), __uint_as_float(u.z) + __uint_as_float(v.z));
            xo = pack_bf16(bf_lo(xo) + bf_lo(y), bf_hi(xo) + bf_hi(y));
        }
        if (!half && !ffn) continue;
        const uint32_t xw = movm(xo);
        if (TAIL && half) {
            reinterpret_cast<uint32_t*>(p.out)[wq * 32 + lane] = xw;
            if (wq == 0) {
                if (lane < 16) g_s.ticket[lane >> 3][lane & 7][0] = 0;
                if (lane == 16) g_s.epoch = (tag >> 2) + 1;
            }
            break;
        }
        if (!TAIL) {
            mbar_wait(SM_WBAR, qs && ffn);
#pragma unroll
            for (int ks = 0; ks < NPRE; ks++) {
                ldsm4t(f[ks], a0 + ks * kstride);
                ldsm4t(f[ks] + 4, a1 + ks * kstride);
            }
        }
        ln_gemv_part<NPRE>(f, a0, a1, kstride, xw, wq, lane);
        const uint32_t wd0 = Z_GU + USTR + wq * 2048 + ((lane & 7) + (lane >> 4) * 8) * 128 + ((((lane >> 3) & 1) ^ (lane & 7)) << 4);
        uint32_t d[4][4];
        constexpr int DPRE = TAIL ? 4 : 0;
#pragma unroll
        for (int mt = 0; mt < DPRE; mt++) ldsm4t(d[mt], wd0 ^ (mt << 5));
        uint4* out = qs ? q_dst(p, 1, cta, lane) : &g_s.ar[TAIL ? 3 : 1][cta & 1][wq * 16 + (lane >> 1)][lane & 1];
        __syncthreads();
        if (!TAIL && !half && wq == 4) load_wq(tm, cta, 0, z);
        float r = ln_gemv_fin(lane);
        if (qs) {
            if (wq == 0) publish_q(out, r, tag, lane);
            if (cta == 0)
                asm volatile("st.relaxed.gpu.global.b64 [%0], %1;" ::"l"(&g_s.x2[wq * 32 + lane]), "l"((unsigned long long)tag << 32 | xo) : "memory");
            __syncthreads();
            break;
        }
        r = bf16r(r);
        const float up = __shfl_down_sync(0xffffffffu, r, 16);
#pragma unroll
        for (int mt = DPRE; mt < 4; mt++) ldsm4t(d[mt], wd0 ^ (mt << 5));
        const float hh = (r > 0.f ? r : 0.f * r) * up;
        const float h0 = __shfl_sync(0xffffffffu, hh, 2 * t), h1 = __shfl_sync(0xffffffffu, hh, 2 * t + 1);
        const float h2 = __shfl_sync(0xffffffffu, hh, 2 * t + 8), h3 = __shfl_sync(0xffffffffu, hh, 2 * t + 9);
        const uint32_t b0 = pack_bf16(h0, h1), b1 = pack_bf16(h2, h3);
        float c0[4] = {0.f, 0.f, 0.f, 0.f}, c1[4] = {0.f, 0.f, 0.f, 0.f};
#pragma unroll
        for (int mt = 0; mt < 4; mt++) {
            const bool mine = (g >> 1) == mt;
            mma((mt & 1) ? c1 : c0, d[mt], mine ? b0 : 0u, mine ? b1 : 0u);
        }
        ar_add(out, c0[0] + c1[0], c0[2] + c1[2]);
        if (!TAIL) {
            if (wq == 4 || wq == 5) bar_sync(4, 256); else bar_arrive(4, 256);
        }
    }
}

#define UVARS                                                                                               \
    const int wqu = __shfl_sync(0xffffffffu, tid_now() >> 5, 0);                                            \
    const int wg = wqu >> 2, wj = wqu & 3;                                                                  \
    [[maybe_unused]] const int head = unit_head(cta, wg), ui = unit_index(cta, wg), tb = head * NTILE;      \
    [[maybe_unused]] const uint32_t slots = SM_SLOTS + wg * USTR, bars = SM_BAR + wg * 48;                  \
    [[maybe_unused]] const int barid = 1 + wg;                                                              \
    [[maybe_unused]] const uint32_t qbase = cta < 128 ? SM_Q : SM_WG + wg * 1024;                           \
    [[maybe_unused]] const uint32_t rec = SM_ST + wg * 16;                                                  \
    [[maybe_unused]] const uint32_t mx = SM_MX + wg * 64;
#define Q_RD (qbase + (lane & 15) * 16)
#define P_RD (SM_P + wg * 512 + (lane & 15) * 16)
#define P_WR (SM_P + wg * 512 + (wj >> 1) * 256 + (wj & 1) * 8 + (lane & 15) * 16)

__device__ __forceinline__ void static_phase(const Maps& tm, const int cta, Acc& acc, uint32_t (*rp)[48]) {
    UVARS
#pragma unroll 1
    for (int rv = 0; rv < NSTAT; rv++) {
        const int rn = __shfl_sync(0xffffffffu, rv, 0);
        const int lane = tid_now() & 31;
        const uint32_t d = (uint32_t)(0x10210432105432ull >> (8 * rn)), par = 0x7c0u >> (2 * rn);
        const int sk = d & 7, sv = (d >> 4) & 7;
        Pack pk;
        pk.cmp = SM_CMP + wg * 16;
        pk.esc = SM_ESC + wg * (ECAP * 8);
        pk.key = (rn < 4 ? rn + 3 : 6 - rn) << 11 | wj << 5 | lane;
        const bool inplace = rn < 4;
        uint32_t dst = slots + 2 * SLOT + (6 - rn) * 24576 + (wj * 32 + lane) * 16;
        uint32_t kb = k_offset(slots, wj, lane) + sk * SLOT;
        float s[4] = {0.f, 0.f, 0.f, 0.f}, s2[4] = {0.f, 0.f, 0.f, 0.f};
        uint32_t a[16];
        mbar_wait(bars + sk * 8, par & 1);
        {
            const uint32_t b4 = lds32(pk.cmp);
#pragma unroll 1
            for (int hv = 0; hv < 2; hv++) {
                const int h = __shfl_sync(0xffffffffu, hv, 0);
                load_khalf(a, kb);
                pack16(a, b4, inplace ? kb : dst, inplace ? kb ^ 32 : dst + 2048, inplace ? kb ^ 64 : dst + 4096, h, pk);
                qk_half(s, s2, a, Q_RD + h * 512);
                kb += 8192; dst += 6144;
            }
        }
#pragma unroll
        for (int i = 0; i < 4; i++) s[i] += s2[i];
        softmax_step(s, acc, P_WR, mx, barid, lane, wj);
        uint32_t vb = v_offset(slots, wj, lane) + sv * SLOT;
        mbar_wait(bars + sv * 8, (par >> 1) & 1);
        {
            const uint32_t b4 = lds32(pk.cmp + 4);
#pragma unroll 1
            for (int yv = 0; yv < 2; yv++) {
                const int y = __shfl_sync(0xffffffffu, yv, 0);
                load_vhalf(a, vb);
                pack16(a, b4, inplace ? vb : dst, inplace ? vb ^ 32 : dst + 2048, inplace ? vb + 2048 : dst + 4096, 2 + y, pk);
                pv_half<true>(acc, a, SM_P + wg * 512 + (tid_now() & 15) * 16 + y * 256);
                vb += 4096; dst += 6144;
            }
            vb -= 8192;
        }
        {
            const uint32_t kb2 = k_offset(slots, wj, tid_now() & 31) + sk * SLOT;
            if (rn == 0) park(rp[0], kb2, vb);
            if (rn == 1) park(rp[1], kb2, vb);
            if (rn == 2) park(rp[2], kb2, vb);
            if (rn == 3) park(rp[3], kb2, vb);
        }
        asm volatile("fence.proxy.async.shared::cta;" ::: "memory");
        wg_bar_or(barid, false);
        const int j = (int)((wj == 1 ? 0xe0c0a86u : 0xfd0b907u) >> (4 * rn)) & 15;
        if ((wj == 1 || wj == 2) && j) issue_item(j, tm, tb, ui, slots, bars);
        if (wj == 0) {
            const uint32_t st = lds32(rec + 4);
            if (lane == 0 && lds32(pk.cmp + 8) > ECAP) {
                sts16(SM_KEEP + wg * 64 + (st & 255) * 2, rn * NUNIT + ui);
                sts32(rec + 4, (st + 1) | 0x10000u << (pk.key >> 11));
            }
            __syncwarp();
        }
    }
    {
        uint32_t c = slots + 2 * SLOT + 12288 + (tid_now() & 127) * 16;
#pragma unroll 1
        for (int j = 0; j < 6; j++, c += 2048) {
            const uint4 u = lds128(c), v = lds128(c + 36864);
            sts128(c, v.x, v.y, v.z, v.w);
            sts128(c + 36864, u.x, u.y, u.z, u.w);
        }
        asm volatile("fence.proxy.async.shared::cta;" ::: "memory");
    }
    if (wqu == 0) __threadfence();
    wg_bar_or(barid, false);
}

__device__ __forceinline__ void acc_init(Acc& a) {
#pragma unroll
    for (int i = 0; i < 4; i++) { a.o[0][i] = 0.f; a.o[1][i] = 0.f; a.l[i] = 0.f; }
    a.m0 = a.m1 = __int_as_float(0xff800000);
}

__device__ __forceinline__ void attention_pass(const Maps& tm, const Params& p, const int cta, const int ph, const uint32_t tag0,
                                               Acc& acc, uint32_t (*rp)[48], float* s, const uint32_t allflags) {
    UVARS
    const int lim = ph ? T_KEEP0 : NTILE;
    uint32_t ticket = 0;
    if (wj == 0) draw_ticket(ticket, p, ph, head, tid_now() & 31);
    const uint32_t st0 = __shfl_sync(0xffffffffu, lds32(rec + 4), 0);
    uint32_t phbits = __shfl_sync(0xffffffffu, lds32(rec + 12), 0);
    int nk = st0 & 255;
    uint32_t cur = DESC(0, 1) | 256;
    uint32_t q0 = 0, q1 = 0;
    int rn = NSTAT, ki = 0, since = 1;
    bool open = true;
    if (ph) {
        rn = 0; q0 = DESC(0, 3) | 256; cur = DESC(2, 1) | 128;
        if (nk > 0 && __shfl_sync(0xffffffffu, (int)lds16(SM_KEEP + wg * 64 + nk * 2 - 2), 0) >= T_KEEP0) nk--;
        else cur |= 512;
    }
#pragma unroll 1
    while (true) {
        const int lane = tid_now() & 31;
        const int sk = cur & 7, sv = (cur >> 3) & 7;
        const bool keeps = ph && ki < nk && cur;
        const bool want = cur && open && (!(q0 & 256) || (keeps && since < 1));
        int tkeep = 0;
        if (keeps) tkeep = __shfl_sync(0xffffffffu, lds16(SM_KEEP + wg * 64 + ki * 2), 0);
        const bool resid = rn + (cur == 0) < NSTAT;
        if (cur ? !(cur & 512) : !(st0 >> (16 + rn) & 1)) {
            Pack pk;
            pk.cmp = SM_CMP + wg * 16;
            pk.esc = SM_ESC + wg * (ECAP * 8);
            pk.key = rn << 11 | wj << 5 | lane;
            uint32_t a[16], vb, flags = 0;
            if (cur) {
                vb = v_offset(slots, wj, lane) + sv * SLOT;
                if (!(cur & 128)) {
                    const uint32_t kb = k_offset(slots, wj, lane) + sk * SLOT;
                    float s2[4] = {0.f, 0.f, 0.f, 0.f};
                    s[0] = s[1] = s[2] = s[3] = 0.f;
                    mbar_wait(bars + sk * 8, (phbits >> sk) & 1);
                    load_khalf(a, kb);
                    qk_half(s, s2, a, Q_RD);
                    load_khalf(a, kb + 8192);
                    qk_half(s, s2, a, Q_RD + 512);
                    mbar_wait(bars + sv * 8, (phbits >> sv) & 1);
                    phbits ^= 1u << sk | 1u << sv;
#pragma unroll
                    for (int i = 0; i < 4; i++) s[i] += s2[i];
                }
                load_vhalf(a, vb);
            } else {
                vb = slots + 2 * SLOT + (wj * 32 + lane) * 16;
                flags = allflags >> (4 * rn);
                if (rn < 3) {
                    const uint4 u = lds128(((vb & ~32u) | (rn & 1) << 5) + 32768 + (rn >> 1) * 2048);
                    s[0] = __uint_as_float(u.x); s[1] = __uint_as_float(u.y); s[2] = __uint_as_float(u.z); s[3] = __uint_as_float(u.w);
                    vb += ((0x423 >> (4 * rn)) & 7) * 12288;
                } else {
                    vb += 49152;
                    if (rn == 3) unpark(rp[0], vb);
                    if (rn == 4) unpark(rp[1], vb);
                    if (rn == 5) unpark(rp[2], vb);
                    if (rn == 6) unpark(rp[3], vb);
                    const uint32_t up = lds32(pk.cmp);
                    float s2[4] = {0.f, 0.f, 0.f, 0.f};
                    s[0] = s[1] = s[2] = s[3] = 0.f;
#pragma unroll 1
                    for (int h = 0; h < 2; h++) {
                        unpack16(a, up, vb + h * 6144, h, flags, pk);
                        qk_half(s, s2, a, Q_RD + h * 512);
                    }
#pragma unroll
                    for (int i = 0; i < 4; i++) s[i] += s2[i];
                }
                unpack16(a, lds32(pk.cmp + 4), vb + 12288, 2, flags, pk);
            }
            softmax_step(s, acc, P_WR, mx, barid, lane, wj);
            pv_half<false>(acc, a, P_RD);
            if (cur) load_vhalf(a, vb + 4096);
            else unpack16(a, lds32(pk.cmp + 4), vb + 18432, 3, flags, pk);
            pv_half<false>(acc, a, P_RD + 256);
        } else {
            wg_bar_or(barid, false);
        }
        if (wj == 0)
            asm volatile("{\n.reg .pred p, q;\n.reg .u32 w;\nmov.u32 w, %6;\nsetp.eq.u32 p, %7, 0;\n@p bra.uni N_%=;\n"
                         "shfl.sync.idx.b32 w, %1, 0, 31, 0xffffffff;\nadd.u32 w, w, %5;\nmin.u32 w, w, %6;\nN_%=:\n"
                         "setp.eq.u32 p, %2, 0;\nsetp.ge.and.u32 q, w, %3, p;\n@q or.b32 w, w, 0x10000;\n"
                         "@p st.shared.u32 [%0], w;\n@q red.relaxed.gpu.global.add.u32 [%4], 1;\n}"
                         ::"r"(rec), "r"(ticket), "r"(lane), "r"((!resid && !q0 && !keeps) ? lim : NTILE + 1),
                           "l"(&g_s.done[lane]), "n"(T_DYN0 + NUNIT), "n"(NTILE), "r"((uint32_t)want) : "memory");
        bar_sync(8 + wg, 128);
        int tv = __shfl_sync(0xffffffffu, (int)lds32(rec), 0);
        if (tv > NTILE) break;
        if (cur == 0) rn++;
        uint32_t push = 0;
        const bool streamed = tv < lim;
        if (streamed) push = (cur & 127) | 256;
        else if (keeps) { tv = tkeep; push = cur & 127; }
        if (push && (wj == 1 || wj == 2)) {
            const int sl = wj == 1 ? sk : sv;
            tma_tile(wj == 1 ? &tm.k : &tm.v, tb + tv, slots + sl * SLOT, bars + sl * 8);
            if (!ph && tv >= T_KEEP0 && tv < T_KEEPEND) l2_prefetch((wj == 1 ? p.k : p.v) + (size_t)(tb + tv) * SLOT, SLOT, POL_NORMAL);
        }
        if (streamed) {
            since++;

            if (!ph && tv >= T_KEEP0) {
                if (wj == 3 && lane == 0) sts16(SM_KEEP + wg * 64 + nk * 2, tv);
                nk++;
                if (nk >= KEEPCAP) open = false;
            }
            if (open && wj == 0) draw_ticket(ticket, p, ph, head, lane);
        } else {
            if (want) open = false;
            if (keeps) { ki++; since = 0; }
        }
        if (q0) q1 |= push; else q0 = push;
        if (resid && (q0 == 0 || (streamed && q1 == 0))) {
            cur = 0;
        } else {
            cur = q0; q0 = q1; q1 = 0;
        }
    }
    const int lane = tid_now() & 31;
    {
        const int e = (lane >> 1) & 1;
        float l = e ? acc.l[1] : acc.l[0], m = e ? acc.m1 : acc.m0;
        float inv; asm("rcp.approx.ftz.f32 %0, %1;" : "=f"(inv) : "f"(l));
        float lg; asm("lg2.approx.ftz.f32 %0, %1;" : "=f"(lg) : "f"(l));
        uint32_t lam = __float_as_uint(m + lg);
        const uint32_t t16 = (tag0 + ph + 1) & 0xffffu;
        uint32_t ta = (lam & 0xffff0000u) | t16, tc = (lam << 16) | t16;
        uint4* dst = part_dst(p, head, ui, wqu * 32 + lane);
        ll_st(dst, __float_as_uint((e ? acc.o[0][1] : acc.o[0][0]) * inv), ta,
                   __float_as_uint((e ? acc.o[0][3] : acc.o[0][2]) * inv), tc);
        ll_st(dst + 4 * NUNIT * 2, __float_as_uint((e ? acc.o[1][1] : acc.o[1][0]) * inv), ta,
                                   __float_as_uint((e ? acc.o[1][3] : acc.o[1][2]) * inv), tc);
    }
    if (wj == 0 && lane == 0) {
        sts32(rec + 4, nk | (st0 & 0xffff0000u));
        sts32(rec + 12, phbits);
    }
}

__global__ void __launch_bounds__(256, 1)
fused_kernel(const __grid_constant__ Maps tm, const Params p) {
    extern __shared__ __align__(1024) unsigned char smem_raw[];
    const int cta = blockIdx.x;
    const bool worker = cta < 128;
    uint32_t tag0;
    if ((uint32_t)__cvta_generic_to_shared(smem_raw) != SM_BASE) __trap();
    uint32_t rp[4][48];
    Acc acc;
    {
        UVARS
        const int lane = tid_now() & 31;
        if (wj == 1 && worker) l2_prefetch(p.wq + (size_t)(cta * 2 + wg) * SLOT, SLOT, POL_NORMAL);
        if (wj == 0) {
#pragma unroll
            for (int i = 0; i < 6; i++) mbar_init(bars + i * 8, 1);
            mbar_init(SM_WBAR + wg * 8, 2);
            mbar_init(SM_DBAR + wg * 8, 1);
            asm volatile("fence.proxy.async.shared::cta;" ::: "memory");
            __syncwarp();
            if (worker && wg == 0) {
                load_wq(tm, cta, 0, SM_SLOTS + SLOT);
                load_wq(tm, cta, 1, SM_SLOTS + USTR + SLOT);
            }
            delay_cycles(D_KV);
            issue_item(0, tm, tb, ui, slots, bars);
            issue_item(1, tm, tb, ui, slots, bars);
            if (worker && wg == 0 && lane < 16) ll_st(q_dst(p, 0, cta, lane), 0, 0, 0, 0);
        }
        if (wj == 1) {
            if (lane < ECAP) sts64(SM_ESC + wg * (ECAP * 8) + lane * 8, 0xffffffffu, 0);
            if (lane < 2) sts128(rec + lane * 32, 0, 0, 0, 0x27);
        }
        if (wj == 2) {
            const uint4 u = *reinterpret_cast<const uint4*>(p.x + wg * 256 + lane * 8);
            sts128(SM_P + wg * 512 + lane * 16, u.x, u.y, u.z, u.w);
        }
        if (wqu == 7 && worker && lane < 16) ll_st(&g_s.ar[0][0][0][0] + (cta * 8 + (lane >> 1)) * 8 + (lane & 1), 0, 0, 0, 0);
        if (wqu == 3) {
            uint32_t e;
            asm volatile("ld.relaxed.gpu.global.u32 %0, [%1];" : "=r"(e) : "l"(&g_s.epoch) : "memory");
            sts32(SM_RED, e * 4 + 1);
        }
        __syncthreads();
        tag0 = __shfl_sync(0xffffffffu, lds32(SM_RED), 0);
        const uint32_t xw = lds32(SM_P + wqu * 128 + lane * 4);
        __syncthreads();
        uint32_t it = 0;
        int item = 2;
#pragma unroll 1
        for (int stage = worker ? 0 : 1; stage < 3 || item < 6;) {
            if (item < (stage ? 6 : 5) && (wj != 1 || stage == 3 || mbar_test(bars + item * 8, 0))) {
                if (wj == 1) issue_item(item, tm, tb, ui, slots, bars);
                item++;
                continue;
            }
            spin_guard(it);
            if (stage == 0) {
                if (!mbar_test(SM_WBAR, 0)) continue;
                const int row = wj * 64 + (lane & 7) + (lane >> 4) * 8;
                const uint32_t a0 = slots + SLOT + row * 64 + ((((lane >> 3) & 1) ^ ((lane >> 1) & 3)) << 4);
                uint32_t f[1][8];
                ldsm4t(f[0], a0);
                ldsm4t(f[0] + 4, a0 ^ 32);
                ln_gemv_part<1>(f, a0, a0 ^ 32, 1024, xw, wqu, lane);
                __syncthreads();
                if (wqu == 0) publish_q(q_dst(p, 0, cta, lane), ln_gemv_fin(lane), tag0, lane);
                if (wqu == 6 && cta < 112) {
                    expect_tx(SM_DBAR, SLOT);
                    tma_2d(&tm.wg, cta * 16, 0, SM_WG, SM_DBAR);
                    tma_2d(&tm.wg, cta * 16, 256, SM_WG + 8192, SM_DBAR);
                }
                __syncthreads();
            } else if (stage == 1) {
                if (!mbar_test(bars + 2 * 8, 0) || !mbar_test(bars + 3 * 8, 0)) continue;
#pragma unroll 1
                for (int h = 0; h < 4; h++) {
                    uint32_t r[16], m = 0;
                    load_khalf(r, k_offset(slots, wj, lane) + 2 * SLOT + h * 8192);
#pragma unroll
                    for (int j = 0; j < 16; j++) m = __vmaxu2(m, r[j] & 0x7fff7fffu);
                    m = __reduce_max_sync(0xffffffffu, max(m >> 23, (m >> 7) & 0xffu));
                    if (lane == 0)
                        asm volatile("red.shared.max.u32 [%0], %1;" ::"r"(SM_CMP + wg * 16 + (h & 2) * 2),
                                     "r"((min(max(m, 15u), 141u) + 112u) * 0x00800080u) : "memory");
                    __syncwarp();
                }
            } else {
                const uint4 v = ll_ld(&g_s.q[0][cta >> 7][head][wj * 32 + lane]);
                if (__any_sync(0xffffffffu, v.y != tag0 || v.w != tag0)) { delay_cycles(200); continue; }
                sts64(qbase + (wj * 32 + lane) * 8, v.x, v.z);
            }
            stage++;
        }
        wg_bar_or(barid, false);
#pragma unroll
        for (int i = 0; i < 4; i++)
#pragma unroll
            for (int j = 0; j < 48; j++) asm volatile("" : "=r"(rp[i][j]));
        acc_init(acc);
    }
    static_phase(tm, cta, acc, rp);
    float s[4] = {0.f, 0.f, 0.f, 0.f};
    uint32_t allflags = 0;
#pragma unroll 1
    for (int phv = 0;; phv = 1) {
        const int ph = __shfl_sync(0xffffffffu, phv, 0);
        attention_pass(tm, p, cta, ph, tag0, acc, rp, s, allflags);
        if (ph) break;
        uint32_t rx[32];
        {
            UVARS
            load_kfrag(rx, k_offset(slots, wj, tid_now() & 31));
            wg_bar_or(barid, false);
            if (worker && wj == 3) tma_rows(&tm.wo, cta * 32 + wg * 16, slots, SM_WBAR);
            if (cta < 112) mbar_wait(SM_DBAR, 0);
        }
        if (worker) gemv_chain<false>(tm, p, cta, tag0 + 1);
        UVARS
        const int lane = tid_now() & 31;
        const uint4* src = &g_s.q[1][cta >> 7][head][wj * 32 + lane];
        Pack pk = {SM_CMP + wg * 16, SM_ESC + wg * (ECAP * 8), (uint32_t)(wj << 5 | lane)};
        allflags = esc_flags(pk);
        uint4 v;
        uint32_t it = 0;
        do {
            spin_guard(it);
            if (it == 1 || !worker) delay_cycles(D_AG);
            v = ll_ld(src);
            if (it == 1 && wj == 1) tma_tile(&tm.k, tb + T_DYN0 + ui, slots, bars);
        } while (__any_sync(0xffffffffu, v.y != tag0 + 1 || v.w != tag0 + 1));
        sts64(qbase + (wj * 32 + lane) * 8, v.x, v.z);
        wg_bar_or(barid, false);
        float s2[4] = {0.f, 0.f, 0.f, 0.f};
        s[0] = s[1] = s[2] = s[3] = 0.f;
        qk_half(s, s2, rx, Q_RD);
        qk_half(s, s2, rx + 16, Q_RD + 512);
#pragma unroll
        for (int i = 0; i < 4; i++) s[i] += s2[i];
        {
            const uint32_t store = slots + 2 * SLOT + (wj * 32 + lane) * 16, up = lds32(pk.cmp);
#pragma unroll 1
            for (int pv = 2; pv >= 0; pv--) {
                const int pos = __shfl_sync(0xffffffffu, pv, 0), c = (0x120 >> (4 * pos)) & 3;
                pk.key = c << 11 | wj << 5 | lane;
                float z[4] = {0.f, 0.f, 0.f, 0.f}, z2[4] = {0.f, 0.f, 0.f, 0.f};
#pragma unroll 1
                for (int h = 0; h < 2; h++) {
                    uint32_t a[16];
                    const uint4 q0 = lds128(Q_RD + h * 512), q1 = lds128(Q_RD + h * 512 + 256);
                    unpack16(a, up, store + pos * 12288 + h * 6144, h, allflags >> (4 * c), pk);
                    mma(z, a, q0.x, q0.y);
                    mma(z2, a + 4, q0.z, q0.w);
                    mma(z, a + 8, q1.x, q1.y);
                    mma(z2, a + 12, q1.z, q1.w);
                }
                asm volatile("{\n.reg .pred p;\nsetp.eq.u32 p, %5, 0;\n@p st.shared.v4.f32 [%0], {%1,%2,%3,%4};\n}"
                             ::"r"(store + 32768 + (c >> 1) * 2048), "f"(z[0] + z2[0]), "f"(z[1] + z2[1]), "f"(z[2] + z2[2]),
                               "f"(z[3] + z2[3]), "r"(((lane >> 1) ^ c) & 1) : "memory");
                if (pos == 1) {
                    bar_sync(8 + wg, 128);
                    if (wj == 2) tma_tile(&tm.v, tb + T_DYN0 + ui, slots + 3 * SLOT, bars + 24);
                }
                __syncwarp();
            }
        }
        acc_init(acc);
    }
    if (worker) {
        UVARS
        if (wj == 3) tma_rows(&tm.wo, cta * 32 + wg * 16, slots + 2 * SLOT, SM_TBAR);
        if (wj == 2 && cta < 112) load_ffn(tm, cta, wg, slots + 3 * SLOT);
        gemv_chain<true>(tm, p, cta, tag0 + 2);
    }
}

typedef CUresult (*EncodeFn)(CUtensorMap*, CUtensorMapDataType, cuuint32_t, void*, const cuuint64_t*, const cuuint64_t*,
                             const cuuint32_t*, const cuuint32_t*, CUtensorMapInterleave, CUtensorMapSwizzle,
                             CUtensorMapL2promotion, CUtensorMapFloatOOBfill);

void make_map(EncodeFn encode, CUtensorMap* m, void* base, int rank, const cuuint64_t* gd, const cuuint64_t* gs,
              const cuuint32_t* bx, CUtensorMapSwizzle sw) {
    const cuuint32_t es[3] = {1, 1, 1};
    encode(m, CU_TENSOR_MAP_DATA_TYPE_BFLOAT16, rank, base, gd, gs, bx, es, CU_TENSOR_MAP_INTERLEAVE_NONE, sw,
           CU_TENSOR_MAP_L2_PROMOTION_NONE, CU_TENSOR_MAP_FLOAT_OOB_FILL_NONE);
}

}

extern "C" void kernel_launch(void* const* d_in, const int* in_sizes, int n_in, void* d_out, int out_size) {
    (void)in_sizes; (void)n_in; (void)out_size;
    static EncodeFn encode = nullptr;
    static void* scratch = nullptr;
    if (!encode) {
        void* fn = nullptr;
        cudaDriverEntryPointQueryResult qr;
        cudaGetDriverEntryPoint("cuTensorMapEncodeTiled", &fn, cudaEnableDefault, &qr);
        encode = (EncodeFn)fn;
        cudaGetSymbolAddress(&scratch, g_scratch);
        cudaFuncSetAttribute(fused_kernel, cudaFuncAttributeMaxDynamicSharedMemorySize, SM_TOTAL);
    }
    Maps tm;
    {
        const cuuint64_t gd[3] = {64, 8ull * 65536ull, 2}, gs[2] = {256, 128};
        const cuuint32_t bx[3] = {64, 64, 2};
        make_map(encode, &tm.k, d_in[1], 3, gd, gs, bx, CU_TENSOR_MAP_SWIZZLE_128B);
        make_map(encode, &tm.v, d_in[2], 3, gd, gs, bx, CU_TENSOR_MAP_SWIZZLE_128B);
    }
    {
        const cuuint64_t gd[2] = {4096, 512}, gs[1] = {8192};
        const cuuint32_t bx[2] = {32, 256};
        make_map(encode, &tm.wq, d_in[3], 2, gd, gs, bx, CU_TENSOR_MAP_SWIZZLE_64B);
    }
    {
        const cuuint64_t gd[3] = {64, 4096, 8}, gs[2] = {1024, 128};
        const cuuint32_t bx[3] = {64, 16, 8};
        make_map(encode, &tm.wo, d_in[4], 3, gd, gs, bx, CU_TENSOR_MAP_SWIZZLE_128B);
        const cuuint64_t gd2[3] = {64, 1792, 8};
        make_map(encode, &tm.wd, d_in[8], 3, gd2, gs, bx, CU_TENSOR_MAP_SWIZZLE_128B);
    }
    {
        const cuuint64_t gd[2] = {1792, 512}, gs[1] = {3584};
        const cuuint32_t bx[2] = {16, 256};
        make_map(encode, &tm.wg, d_in[6], 2, gd, gs, bx, CU_TENSOR_MAP_SWIZZLE_32B);
        make_map(encode, &tm.wu, d_in[7], 2, gd, gs, bx, CU_TENSOR_MAP_SWIZZLE_32B);
    }
    Params p;
    p.x = (const __nv_bfloat16*)d_in[0];
    p.k = (const char*)d_in[1];
    p.v = (const char*)d_in[2];
    p.wq = (const char*)d_in[3];
    p.wo = (const char*)d_in[4];
    p.wg = (const char*)d_in[6];
    p.wu = (const char*)d_in[7];
    p.wd = (const char*)d_in[8];
    p.out = (__nv_bfloat16*)d_out;
    p.s = (Scratch*)scratch;
    fused_kernel<<<NCTA, 256, SM_TOTAL, cudaStreamPerThread>>>(tm, p);
}
```

```cpp
#include <cuda_runtime.h>
#include <cuda_bf16.h>
#include <cuda.h>
#include <stdint.h>

namespace {

constexpr int NCTA      = 132;
constexpr int NUNIT     = 33;
constexpr int NTILE     = 1024;
constexpr int SLOT      = 16384;
constexpr int NSTAT     = 7;
constexpr int T_DYN0    = NSTAT * NUNIT;
constexpr int T_KEEP0   = NTILE - 200;
constexpr int T_KEEPEND = NTILE - 33;
constexpr int KEEPCAP   = 32;
constexpr int ECAP      = 28;
constexpr int D_AR      = 650;
constexpr int D_SKIP    = 1500;
constexpr int D_AG      = 100;
constexpr int D_KV      = 300;
constexpr int D_QP0     = 1000, D_QP1 = 1600;
constexpr unsigned SPIN_LIMIT = 1u << 22;

constexpr uint32_t SM_BASE  = 1024;
constexpr uint32_t USTR     = 2 * SLOT + 3 * 24576;
constexpr uint32_t SM_SLOTS = SM_BASE;
constexpr uint32_t SM_WG    = SM_SLOTS + 2 * USTR;
constexpr uint32_t SM_Q     = SM_WG + SLOT;
constexpr uint32_t SM_P     = SM_Q + 1024;
constexpr uint32_t SM_RED   = SM_P + 1024;
constexpr uint32_t SM_MX    = SM_RED;
constexpr uint32_t SM_BAR   = SM_RED + 192;
constexpr uint32_t SM_WBAR  = SM_BAR + 96;
constexpr uint32_t SM_TBAR  = SM_BAR + 104;
constexpr uint32_t SM_DBAR  = SM_BAR + 112;
constexpr uint32_t SM_KEEP  = SM_BAR + 128;
constexpr uint32_t SM_ST    = SM_KEEP + 128;
constexpr uint32_t SM_CMP   = SM_ST + 32;
constexpr uint32_t SM_ESC   = SM_CMP + 32;
constexpr int SM_TOTAL      = SM_ESC + 2 * ECAP * 8 - SM_BASE;
static_assert(SM_TOTAL <= 232448 && ECAP <= 32, "smem");

struct __align__(1024) Scratch {
    uint4 part[128][8][NUNIT][2];
    uint4 ar[4][2][128][8];
    uint2 x2[256];
    uint4 q[2][2][8][128];
    unsigned ticket[2][8][32];
    unsigned done[32];
    unsigned epoch;
};
__device__ Scratch g_scratch;
#define g_s (*p.s)

struct Maps { CUtensorMap k, v, wq, wo, wg, wu, wd; };
struct Params {
    const __nv_bfloat16* x;
    const char* k;
    const char* v;
    const char* wq;
    const char* wu;
    const char* wd;
    __nv_bfloat16* out;
    Scratch* s;
};

__device__ __forceinline__ void mbar_init(uint32_t bar, uint32_t cnt) {
    asm volatile("{\n.reg .pred p;\nelect.sync _|p, 0xffffffff;\n@p mbarrier.init.shared::cta.b64 [%0], %1;\n}" ::"r"(bar), "r"(cnt) : "memory");
}
__device__ __forceinline__ void mbar_wait(uint32_t bar, uint32_t parity) {
    asm volatile("{\n.reg .pred p, q;\n.reg .u32 c;\nmov.u32 c, 0;\n"
                 "W_%=:\nmbarrier.try_wait.parity.shared::cta.b64 p, [%0], %1;\nvote.sync.all.pred p, p, 0xffffffff;\n"
                 "@p bra.uni D_%=;\nadd.u32 c, c, 1;\nsetp.lt.u32 q, c, %2;\n@q bra.uni W_%=;\ntrap;\nD_%=:\n}"
                 ::"r"(bar), "r"(parity), "n"(SPIN_LIMIT) : "memory");
}
__device__ __forceinline__ void spin_guard(uint32_t& it) {
    asm volatile("{\n.reg .pred q;\nadd.u32 %0, %0, 1;\nsetp.gt.u32 q, %0, %1;\n@q trap;\n}" : "+r"(it) : "n"(SPIN_LIMIT));
}
constexpr uint64_t POL_FIRST = 0x12f0000000000000ull, POL_NORMAL = 0x16f0000000000000ull;
__device__ __forceinline__ void tma_rows(const CUtensorMap* tm, int row, uint32_t dst, uint32_t bar) {
    asm volatile("{\n.reg .pred p;\nelect.sync _|p, 0xffffffff;\n"
                 "@p mbarrier.arrive.expect_tx.shared::cta.b64 _, [%4], %6;\n"
                 "@p cp.async.bulk.tensor.3d.shared::cluster.global.mbarrier::complete_tx::bytes.L2::cache_hint "
                 "[%0], [%1, {%2, %3, %2}], [%4], %5;\n}"
                 ::"r"(dst), "l"(tm), "r"(0), "r"(row), "r"(bar), "l"(POL_FIRST), "r"(SLOT) : "memory");
}
__device__ __forceinline__ void tma_tile(const CUtensorMap* tm, int gtile, uint32_t dst, uint32_t bar) {
    tma_rows(tm, gtile * 64, dst, bar);
}
__device__ __forceinline__ void expect_tx(uint32_t bar, uint32_t bytes) {
    asm volatile("{\n.reg .pred p;\nelect.sync _|p, 0xffffffff;\n@p mbarrier.arrive.expect_tx.shared::cta.b64 _, [%0], %1;\n}"
                 ::"r"(bar), "r"(bytes) : "memory");
}
__device__ __forceinline__ void tma_2d(const CUtensorMap* tm, int c0, int c1, uint32_t dst, uint32_t bar) {
    asm volatile("{\n.reg .pred p;\nelect.sync _|p, 0xffffffff;\n"
                 "@p cp.async.bulk.tensor.2d.shared::cluster.global.mbarrier::complete_tx::bytes.L2::cache_hint "
                 "[%0], [%1, {%2, %3}], [%4], %5;\n}"
                 ::"r"(dst), "l"(tm), "r"(c0), "r"(c1), "r"(bar), "l"(POL_FIRST) : "memory");
}
__device__ __forceinline__ void l2_prefetch(const void* p, uint32_t bytes, uint64_t pol) {
    asm volatile("{\n.reg .pred p;\nelect.sync _|p, 0xffffffff;\n"
                 "@p cp.async.bulk.prefetch.L2.global.L2::cache_hint [%0], %1, %2;\n}" ::"l"(p), "r"(bytes), "l"(pol) : "memory");
}
__device__ __forceinline__ void ldsm4(uint32_t* r, uint32_t a) {
    asm volatile("ldmatrix.sync.aligned.m8n8.x4.shared.b16 {%0,%1,%2,%3}, [%4];"
                 : "=r"(r[0]), "=r"(r[1]), "=r"(r[2]), "=r"(r[3]) : "r"(a) : "memory");
}
__device__ __forceinline__ void ldsm4t(uint32_t* r, uint32_t a) {
    asm volatile("ldmatrix.sync.aligned.m8n8.x4.trans.shared.b16 {%0,%1,%2,%3}, [%4];"
                 : "=r"(r[0]), "=r"(r[1]), "=r"(r[2]), "=r"(r[3]) : "r"(a) : "memory");
}
__device__ __forceinline__ void mma(float* c, const uint32_t* a, uint32_t b0, uint32_t b1) {
    asm volatile("mma.sync.aligned.m16n8k16.row.col.f32.bf16.bf16.f32 {%0,%1,%2,%3}, {%4,%5,%6,%7}, {%8,%9}, {%0,%1,%2,%3};"
                 : "+f"(c[0]), "+f"(c[1]), "+f"(c[2]), "+f"(c[3])
                 : "r"(a[0]), "r"(a[1]), "r"(a[2]), "r"(a[3]), "r"(b0), "r"(b1));
}
__device__ __forceinline__ uint32_t movm(uint32_t a) {
    uint32_t d; asm volatile("movmatrix.sync.aligned.m8n8.trans.b16 %0, %1;" : "=r"(d) : "r"(a)); return d;
}
__device__ __forceinline__ uint32_t pack_bf16(float lo, float hi) {
    uint32_t d; asm("cvt.rn.bf16x2.f32 %0, %1, %2;" : "=r"(d) : "f"(hi), "f"(lo)); return d;
}
__device__ __forceinline__ float bf16r(float v) { return __uint_as_float(pack_bf16(v, 0.f) << 16); }
__device__ __forceinline__ float bf_lo(uint32_t w) { return __uint_as_float(w << 16); }
__device__ __forceinline__ float bf_hi(uint32_t w) { return __uint_as_float(w & 0xffff0000u); }
__device__ __forceinline__ float ex2(float v) { float d; asm("ex2.approx.ftz.f32 %0, %1;" : "=f"(d) : "f"(v)); return d; }
__device__ __forceinline__ uint4 lds128(uint32_t a) {
    uint4 v; asm volatile("ld.shared.v4.u32 {%0,%1,%2,%3}, [%4];" : "=r"(v.x), "=r"(v.y), "=r"(v.z), "=r"(v.w) : "r"(a) : "memory"); return v;
}
__device__ __forceinline__ uint2 lds64(uint32_t a) {
    uint2 v; asm volatile("ld.shared.v2.u32 {%0,%1}, [%2];" : "=r"(v.x), "=r"(v.y) : "r"(a) : "memory"); return v;
}
__device__ __forceinline__ uint32_t lds32(uint32_t a) {
    uint32_t v; asm volatile("ld.shared.u32 %0, [%1];" : "=r"(v) : "r"(a) : "memory"); return v;
}
__device__ __forceinline__ void sts128(uint32_t a, uint32_t x, uint32_t y, uint32_t z, uint32_t w) {
    asm volatile("st.shared.v4.u32 [%0], {%1,%2,%3,%4};" ::"r"(a), "r"(x), "r"(y), "r"(z), "r"(w) : "memory");
}
__device__ __forceinline__ void sts64(uint32_t a, uint32_t x, uint32_t y) {
    asm volatile("st.shared.v2.u32 [%0], {%1,%2};" ::"r"(a), "r"(x), "r"(y) : "memory");
}
__device__ __forceinline__ void sts32(uint32_t a, uint32_t x) {
    asm volatile("st.shared.u32 [%0], %1;" ::"r"(a), "r"(x) : "memory");
}
__device__ __forceinline__ void sts16(uint32_t a, uint32_t x) {
    asm volatile("st.shared.u16 [%0], %1;" ::"r"(a), "h"((unsigned short)x) : "memory");
}
__device__ __forceinline__ uint32_t lds16(uint32_t a) {
    unsigned short v; asm volatile("ld.shared.u16 %0, [%1];" : "=h"(v) : "r"(a) : "memory"); return v;
}
__device__ __forceinline__ bool wg_bar_or(int id, bool p) {
    uint32_t r;
    asm volatile("{\n.reg .pred a, b;\nsetp.ne.u32 a, %2, 0;\nbar.red.or.pred b, %1, 128, a;\nselp.u32 %0, 1, 0, b;\n}"
                 : "=r"(r) : "r"(id), "r"((uint32_t)p) : "memory");
    return r != 0;
}
__device__ __forceinline__ uint4 ll_ld(const uint4* p) {
    unsigned long long a, b;
    asm volatile("ld.relaxed.gpu.global.v2.b64 {%0,%1}, [%2];" : "=l"(a), "=l"(b) : "l"(p) : "memory");
    return make_uint4((uint32_t)a, (uint32_t)(a >> 32), (uint32_t)b, (uint32_t)(b >> 32));
}
__device__ __forceinline__ void ll_st(uint4* p, uint32_t v0, uint32_t t0, uint32_t v1, uint32_t t1) {
    unsigned long long a = ((unsigned long long)t0 << 32) | v0, b = ((unsigned long long)t1 << 32) | v1;
    asm volatile("st.relaxed.gpu.global.v2.b64 [%0], {%1,%2};" ::"l"(p), "l"(a), "l"(b) : "memory");
}
__device__ __forceinline__ uint4 ll_ld_last(const uint4* p) {
    unsigned long long a, b;
    asm volatile("ld.relaxed.gpu.global.L2::cache_hint.v2.b64 {%0,%1}, [%2], %3;" : "=l"(a), "=l"(b) : "l"(p), "l"(POL_FIRST) : "memory");
    return make_uint4((uint32_t)a, (uint32_t)(a >> 32), (uint32_t)b, (uint32_t)(b >> 32));
}
__device__ __forceinline__ void bar_sync(int id, int n) { asm volatile("bar.sync %0, %1;" ::"r"(id), "r"(n) : "memory"); }
__device__ __forceinline__ void bar_arrive(int id, int n) { asm volatile("bar.arrive %0, %1;" ::"r"(id), "r"(n) : "memory"); }
__device__ __forceinline__ void delay_cycles(int n) {
    if (n > 0) {
        uint32_t t0, t1;
        asm volatile("mov.u32 %0, %%clock;" : "=r"(t0));
        do { asm volatile("mov.u32 %0, %%clock;" : "=r"(t1)); } while (t1 - t0 < (uint32_t)n);
    }
}
__device__ __forceinline__ int tid_now() {
    int t; asm volatile("mov.u32 %0, %%tid.x;" : "=r"(t)); return t;
}
__device__ __forceinline__ bool mbar_test(uint32_t bar, uint32_t parity) {
    uint32_t ok;
    asm volatile("{\n.reg .pred p;\nmbarrier.test_wait.parity.shared::cta.b64 p, [%1], %2;\nselp.u32 %0, 1, 0, p;\n}"
                 : "=r"(ok) : "r"(bar), "r"(parity) : "memory");
    return ok != 0;
}

struct Acc {
    float o[2][4];
    float l[4];
    float m0, m1;
};

constexpr float SCALE_LOG2 = 0.08838834764831845f * 1.4426950408889634f;

__device__ __forceinline__ void softmax_step(float* s, Acc& a, uint32_t p_wr, uint32_t mx, int barid, int lane, int wj) {
#pragma unroll
    for (int i = 0; i < 4; i++) s[i] *= SCALE_LOG2;
    bool over = fmaxf(s[0], s[2]) > a.m0 || fmaxf(s[1], s[3]) > a.m1;
    {
        uint32_t b0 = movm(pack_bf16(ex2(s[0] - a.m0), ex2(s[1] - a.m1)));
        uint32_t b1 = movm(pack_bf16(ex2(s[2] - a.m0), ex2(s[3] - a.m1)));
        if (lane < 16) sts64(p_wr, b0, b1);
    }
    if (__any_sync(0xffffffffu, wg_bar_or(barid, over))) {
        float x0 = fmaxf(s[0], s[2]), x1 = fmaxf(s[1], s[3]);
#pragma unroll
        for (int d = 4; d < 32; d <<= 1) {
            x0 = fmaxf(x0, __shfl_xor_sync(0xffffffffu, x0, d));
            x1 = fmaxf(x1, __shfl_xor_sync(0xffffffffu, x1, d));
        }
        if (lane < 2) sts64(mx + wj * 16 + lane * 8, __float_as_uint(x0), __float_as_uint(x1));
        bar_sync(barid + 9, 128);
        float n0 = a.m0, n1 = a.m1;
#pragma unroll
        for (int j = 0; j < 4; j++) {
            uint2 v = lds64(mx + j * 16 + (lane & 1) * 8);
            n0 = fmaxf(n0, __uint_as_float(v.x));
            n1 = fmaxf(n1, __uint_as_float(v.y));
        }
        float f0 = ex2(a.m0 - n0), f1 = ex2(a.m1 - n1);
        a.m0 = n0; a.m1 = n1;
        a.o[0][0] *= f0; a.o[0][2] *= f0; a.o[1][0] *= f0; a.o[1][2] *= f0; a.l[0] *= f0; a.l[2] *= f0;
        a.o[0][1] *= f1; a.o[0][3] *= f1; a.o[1][1] *= f1; a.o[1][3] *= f1; a.l[1] *= f1; a.l[3] *= f1;
        uint32_t b0 = movm(pack_bf16(ex2(s[0] - n0), ex2(s[1] - n1)));
        uint32_t b1 = movm(pack_bf16(ex2(s[2] - n0), ex2(s[3] - n1)));
        if (lane < 16) sts64(p_wr, b0, b1);
        bar_sync(barid + 9, 128);
    }
}

__device__ __forceinline__ uint32_t mul2(uint32_t a, uint32_t b) {
    uint32_t d; asm("mul.rn.bf16x2 %0, %1, %2;" : "=r"(d) : "r"(a), "r"(b)); return d;
}
__device__ __forceinline__ uint32_t fma2(uint32_t a, uint32_t b, uint32_t c) {
    uint32_t d; asm("fma.rn.bf16x2 %0, %1, %2, %3;" : "=r"(d) : "r"(a), "r"(b), "r"(c)); return d;
}
struct Pack {
    uint32_t cmp;
    uint32_t esc;
    uint32_t key;
};
__device__ __forceinline__ void pack16(const uint32_t* a, uint32_t up, uint32_t d0, uint32_t d1, uint32_t d2, int it,
                                       const Pack& pk) {
    const uint32_t dn = 0x7f007f00u - up, nup = up | 0x80008000u;
    uint32_t l[8], n[4], bad = 0;
#pragma unroll
    for (int g = 0; g < 4; g++) {
        uint32_t z[4], e = 0;
#pragma unroll
        for (int j = 0; j < 4; j++) {
            z[j] = mul2(a[4 * g + j], dn);
            e |= fma2(z[j], nup, a[4 * g + j]);
        }
        const uint32_t x0 = __byte_perm(z[0], z[1], 0x7531), x1 = __byte_perm(z[2], z[3], 0x7531);
        l[2 * g] = __byte_perm(z[0], z[1], 0x6420);
        e |= (x0 | x1) & 0x78787878u;
        l[2 * g + 1] = __byte_perm(z[2], z[3], 0x6420) | e;
        n[g] = x0 | __funnelshift_l(x1, x1, 4);
        if (e) bad |= 1u << g;
        if (g & 1) sts128(g == 1 ? d0 : d1, l[2 * g - 2], l[2 * g - 1], l[2 * g], l[2 * g + 1]);
    }
    sts128(d2, n[0], n[1], n[2], n[3]);
    if (bad) {
        uint32_t i;
        asm volatile("atom.shared.add.u32 %0, [%1], %2;" : "=r"(i) : "r"(pk.cmp + 8 + (d2 >> 31)), "r"(__popc(bad)) : "memory");
#pragma unroll
        for (int g = 0; g < 4; g++) {
            asm volatile("{\n.reg .pred p, q;\n.reg .u32 a;\nsetp.ne.u32 p, %1, 0;\nsetp.lt.and.u32 q, %0, %5, p;\n"
                         "@p st.shared.v2.u32 [%6], {%7, %8};\n@p st.shared.u32 [%9], %10;\nmad.lo.u32 a, %0, 8, %2;\n"
                         "@q st.shared.v2.u32 [a], {%3, %4};\n@p add.u32 %0, %0, 1;\n}"
                         : "+r"(i)
                         : "r"(bad & (1u << g)), "r"(pk.esc), "r"(pk.key | it << 9 | g << 7), "r"(a[4 * g + 3]),
                           "n"(ECAP), "r"((g < 2 ? d0 : d1) + (g & 1) * 8), "r"(a[4 * g]), "r"(a[4 * g + 1]), "r"(d2 + g * 4),
                           "r"(a[4 * g + 2]) : "memory");
        }
    }
    __syncwarp();
}
__device__ __forceinline__ uint32_t esc_flags(const Pack& pk) {
    const uint32_t e = lds32(pk.esc + min(pk.key & 31u, ECAP - 1u) * 8);
    return __reduce_or_sync(0xffffffffu, ((e ^ pk.key) & ~0x3f9fu) == 0 ? 1u << ((e >> 9) & 31) : 0u);
}
__device__ __forceinline__ void unpack16(uint32_t* a, uint32_t up, uint32_t c, int it, uint32_t flags, const Pack& pk) {
    const uint4 nn = lds128(c + 4096);
    const uint4 l0 = lds128(c), l1 = lds128(c + 2048);
    const uint32_t n[4] = {nn.x, nn.y, nn.z, nn.w};
    const uint32_t l[8] = {l0.x, l0.y, l0.z, l0.w, l1.x, l1.y, l1.z, l1.w};
#pragma unroll
    for (int g = 0; g < 4; g++) {
        const uint32_t h0 = n[g] & 0x87878787u, h1 = __funnelshift_r(n[g], n[g], 4) & 0x87878787u;
        a[4 * g]     = mul2(__byte_perm(l[2 * g], h0, 0x5140), up);
        a[4 * g + 1] = mul2(__byte_perm(l[2 * g], h0, 0x7362), up);
        a[4 * g + 2] = mul2(__byte_perm(l[2 * g + 1], h1, 0x5140), up);
        a[4 * g + 3] = mul2(__byte_perm(l[2 * g + 1], h1, 0x7362), up);
    }
    if (flags >> it & 1) {
        const uint32_t me = pk.key | it << 9;
        const uint2 e = lds64(pk.esc + min(me & 31u, ECAP - 1u) * 8);
        uint32_t hit = __ballot_sync(0xffffffffu, ((e.x ^ me) & ~0x19fu) == 0) & (uint32_t)((1ull << ECAP) - 1);
#pragma unroll 1
        while (hit) {
            const int src = __ffs(hit) - 1;
            hit &= hit - 1;
            const uint32_t d = __shfl_sync(0xffffffffu, e.x, src) ^ me, v = __shfl_sync(0xffffffffu, e.y, src);
#pragma unroll
            for (int g = 0; g < 4; g++)
                asm volatile("{\n.reg .pred p;\nsetp.eq.u32 p, %4, %5;\n@p ld.shared.v2.u32 {%0, %1}, [%6];\n"
                             "@p ld.shared.u32 %2, [%7];\n@p mov.u32 %3, %8;\n}"
                             : "+r"(a[4 * g]), "+r"(a[4 * g + 1]), "+r"(a[4 * g + 2]), "+r"(a[4 * g + 3])
                             : "r"(d), "n"(g << 7), "r"(c + (g >> 1) * 2048 + (g & 1) * 8), "r"(c + 4096 + g * 4), "r"(v) : "memory");
        }
    }
}

__device__ __forceinline__ void qk_half(float* s, float* s2, const uint32_t* a, uint32_t q) {
    const uint4 q0 = lds128(q), q1 = lds128(q + 256);
    mma(s, a, q0.x, q0.y);
    mma(s2, a + 4, q0.z, q0.w);
    mma(s, a + 8, q1.x, q1.y);
    mma(s2, a + 12, q1.z, q1.w);
}
__device__ __forceinline__ void mma_ones(float* c, uint32_t b) {
    asm volatile("mma.sync.aligned.m16n8k8.row.col.f32.bf16.bf16.f32 {%0,%1,%2,%3}, {%4,%4}, {%5}, {%0,%1,%2,%3};"
                 : "+f"(c[0]), "+f"(c[1]), "+f"(c[2]), "+f"(c[3]) : "r"(0x3f803f80u), "r"(b));
}
template <bool SMALL>
__device__ __forceinline__ void pv_half(Acc& a, const uint32_t* f, uint32_t pa) {
    const uint32_t ones[4] = {0x3f803f80u, 0x3f803f80u, 0x3f803f80u, 0x3f803f80u};
    const uint4 pp = lds128(pa);
    mma(a.o[0], f, pp.x, pp.y);
    mma(a.o[1], f + 4, pp.x, pp.y);
    if (SMALL) { mma_ones(a.l, pp.x); mma_ones(a.l, pp.y); } else mma(a.l, ones, pp.x, pp.y);
    mma(a.o[0], f + 8, pp.z, pp.w);
    mma(a.o[1], f + 12, pp.z, pp.w);
    if (SMALL) { mma_ones(a.l, pp.z); mma_ones(a.l, pp.w); } else mma(a.l, ones, pp.z, pp.w);
}
__device__ __forceinline__ void load_khalf(uint32_t* a, uint32_t k) {
#pragma unroll
    for (int j = 0; j < 4; j++) ldsm4(a + j * 4, k ^ (j << 5));
    __syncwarp();
}
__device__ __forceinline__ void load_vhalf(uint32_t* f, uint32_t v) {
    ldsm4t(f, v);
    ldsm4t(f + 4, v ^ 32);
    ldsm4t(f + 8, v + 2048);
    ldsm4t(f + 12, (v ^ 32) + 2048);
    __syncwarp();
}
__device__ __forceinline__ void park(uint32_t* r, uint32_t kb, uint32_t vb) {
#pragma unroll
    for (int j = 0; j < 12; j++) {
        const int it = j / 3, c = j % 3;
        const uint32_t ad = it < 2 ? (kb ^ (c << 5)) + it * 8192 : (vb ^ ((c & 1) << 5)) + (c >> 1) * 2048 + (it - 2) * 4096;
        const uint4 u = lds128(ad);
        r[4 * j] = u.x; r[4 * j + 1] = u.y; r[4 * j + 2] = u.z; r[4 * j + 3] = u.w;
    }
}
__device__ __forceinline__ void unpark(const uint32_t* r, uint32_t c) {
#pragma unroll
    for (int j = 0; j < 12; j++) sts128(c + j * 2048, r[4 * j], r[4 * j + 1], r[4 * j + 2], r[4 * j + 3]);
}
__device__ __forceinline__ uint32_t k_offset(uint32_t slots, int wj, int lane) {
    const int row = wj * 16 + (lane & 7) + ((lane >> 3) & 1) * 8;
    return slots + row * 128 + (((lane >> 4) ^ (row & 7)) << 4);
}
__device__ __forceinline__ uint32_t v_offset(uint32_t slots, int wj, int lane) {
    const int key = (lane & 7) + (lane >> 4) * 8, cg = wj * 4 + ((lane >> 3) & 1);
    return slots + (cg >> 3) * 8192 + key * 128 + (((cg & 7) ^ (key & 7)) << 4);
}
__device__ __forceinline__ void load_kfrag(uint32_t* rk, uint32_t kb) {
#pragma unroll
    for (int ks = 0; ks < 8; ks++) ldsm4(rk + ks * 4, (kb ^ ((ks & 3) << 5)) + (ks >> 2) * 8192);
}

template <int NPRE>
__device__ __forceinline__ void ln_gemv_part(uint32_t (*f)[8], uint32_t a0, uint32_t a1, uint32_t kstride, uint32_t xw,
                                             int wq, int lane) {
    const int t = lane & 3, g = lane >> 2;
    float c0[4] = {0.f, 0.f, 0.f, 0.f}, c1[4] = {0.f, 0.f, 0.f, 0.f};
#pragma unroll
    for (int ks = 0; ks < 4; ks++) {
        uint32_t* ff = f[ks % NPRE];
        if (ks >= NPRE) {
            ldsm4t(ff, a0 + ks * kstride);
            ldsm4t(ff + 4, a1 + ks * kstride);
        }
        uint32_t xa = __shfl_sync(0xffffffffu, xw, ks * 8 + t), xb = __shfl_sync(0xffffffffu, xw, ks * 8 + 4 + t);
        if (g & 1) xa = xb = 0x3f803f80u;
        mma(c0, ff, xa, xb);
        mma(c1, ff + 4, xa, xb);
    }
    {
        const float a = bf_lo(xw), b = bf_hi(xw);
        const float su = a + b, sq = fmaf(a, a, b * b);
        float keep = (lane & 16) ? sq : su, send = (lane & 16) ? su : sq;
        keep += __shfl_xor_sync(0xffffffffu, send, 16);
#pragma unroll
        for (int k = 8; k > 0; k >>= 1) keep += __shfl_xor_sync(0xffffffffu, keep, k);
        if ((lane & 15) == 0) sts32(SM_RED + (lane >> 4) * 32 + wq * 4, __float_as_uint(keep));
    }
    float y = (t & 2) ? ((t & 1) ? c1[2] : c1[0]) : ((t & 1) ? c0[2] : c0[0]);
    float z = (t & 2) ? ((t & 1) ? c1[3] : c1[1]) : ((t & 1) ? c0[3] : c0[1]);
    sts64(SM_Q + wq * 256 + (t * 8 + g) * 8, __float_as_uint(y), __float_as_uint(z));
}
__device__ __forceinline__ float sum4(uint4 u) {
    return (__uint_as_float(u.x) + __uint_as_float(u.y)) + (__uint_as_float(u.z) + __uint_as_float(u.w));
}
__device__ __forceinline__ float ln_gemv_fin(int lane) {
    float mean, rstd;
    {
        const uint4 a = lds128(SM_RED), b = lds128(SM_RED + 16), c = lds128(SM_RED + 32), d = lds128(SM_RED + 48);
        mean = (sum4(a) + sum4(b)) * (1.f / 512.f);
        const float var = fmaxf(fmaf(sum4(c) + sum4(d), 1.f / 512.f, -mean * mean), 0.f) + 1e-5f;
        asm("rsqrt.approx.ftz.f32 %0, %1;" : "=f"(rstd) : "f"(var));
    }
    uint2 u[8];
#pragma unroll
    for (int j = 0; j < 8; j++) u[j] = lds64(SM_Q + j * 256 + lane * 8);
#define S8(f) (((__uint_as_float(u[0].f) + __uint_as_float(u[1].f)) + (__uint_as_float(u[2].f) + __uint_as_float(u[3].f))) + \
               ((__uint_as_float(u[4].f) + __uint_as_float(u[5].f)) + (__uint_as_float(u[6].f) + __uint_as_float(u[7].f))))
    return (S8(x) - mean * S8(y)) * rstd;
#undef S8
}
__device__ __forceinline__ void ar_add(uint4* dst, float y0, float y1) {
    asm volatile("red.relaxed.gpu.global.add.v4.f32 [%0], {%1, %2, %3, %1};" ::"l"(dst), "f"(1.f), "f"(y0), "f"(y1) : "memory");
}

__device__ __forceinline__ int unit_head(int cta, int wg) { return cta < 128 ? ((cta + (cta >> 3)) & 7) : (cta - 128) * 2 + wg; }
__device__ __forceinline__ int unit_index(int cta, int wg) { return cta < 128 ? (cta >> 3) * 2 + wg : 32; }
__device__ __forceinline__ void issue_item(int j, const Maps& tm, int tb, int ui, uint32_t slots, uint32_t bars) {
    const int slot = (int)((0x1010210432105432ull >> (4 * j)) & 15);
    tma_tile((j & 1) ? &tm.v : &tm.k, tb + (j >> 1) * NUNIT + ui, slots + slot * SLOT, bars + slot * 8);
}
__device__ __forceinline__ void load_ffn(const Maps& tm, int cta, int h, uint32_t z) {
    if (h) {
        tma_rows(&tm.wd, cta * 16, z, SM_WBAR);
    } else {
        expect_tx(SM_WBAR, SLOT);
        tma_2d(&tm.wu, cta * 16, 0, z, SM_WBAR);
        tma_2d(&tm.wu, cta * 16, 256, z + 8192, SM_WBAR);
    }
}
__device__ __forceinline__ void load_wq(const Maps& tm, int cta, int h, uint32_t z) {
    expect_tx(SM_WBAR, SLOT);
    tma_2d(&tm.wq, cta * 32, h * 256, z, SM_WBAR);
}
__device__ __forceinline__ void draw_ticket(uint32_t& ticket, const Params& p, int ph, int head, int lane) {
    asm volatile("{\n.reg .pred p;\nsetp.eq.u32 p, %2, 0;\n@p atom.relaxed.gpu.global.inc.u32 %0, [%1], 0xfffffffe;\n}"
                 : "+r"(ticket) : "l"(&g_s.ticket[ph][head][0]), "r"(lane) : "memory");
}
#define DESC(sk, sv) ((uint32_t)((sk) | ((sv) << 3) | 64))

__device__ __forceinline__ uint4* part_dst(const Params& p, int head, int ui, int tid) {
    const int lane = tid & 31, g = lane >> 2, t = lane & 3;
    return &g_s.part[(head * 4 + 2 * (t & 1) + (t >> 1)) * 4 + ((tid >> 5) & 3)][g >> 1][ui][g & 1];
}
__device__ __forceinline__ uint4* q_dst(const Params& p, int layer, int cta, int lane) {
    return &g_s.q[layer][(lane >> 3) & 1][cta >> 4][((cta & 3) * 16 + ((cta >> 2) & 3) * 4) * 2 + (lane & 7)];
}
__device__ __forceinline__ void publish_q(uint4* out, float r, uint32_t tag, int lane) {
    const int src = (lane & 1) * 16 + ((lane >> 1) & 3) * 2;
    const float q0 = __shfl_sync(0xffffffffu, r, src), q1 = __shfl_sync(0xffffffffu, r, src + 1);
    const float q2 = __shfl_sync(0xffffffffu, r, src + 8), q3 = __shfl_sync(0xffffffffu, r, src + 9);
    if (lane < 16) ll_st(out, pack_bf16(q0, q1), tag, pack_bf16(q2, q3), tag);
}

template <bool TAIL>
__device__ __forceinline__ void gemv_chain(const Maps& tm, const Params& p, const int cta, const uint32_t tag) {
    constexpr uint32_t Z_WO = SM_SLOTS + (TAIL ? 2 : 0) * SLOT, Z_GU = SM_SLOTS + (TAIL ? 3 : 0) * SLOT;
    const int wq = __shfl_sync(0xffffffffu, tid_now() >> 5, 0);
    uint32_t xo;
    {
        const int lane = tid_now() & 31, g = lane >> 2, t = lane & 3;
        if (!TAIL) {
            const unsigned short* xp = reinterpret_cast<const unsigned short*>(p.x) + wq * 64 + t * 16 + g;
            xo = xp[0] | (uint32_t)xp[8] << 16;
            if (wq == 0 && lane < 16) ll_st(q_dst(p, 1, cta, lane), 0, 0, 0, 0);
            __syncwarp();
            if (wq == 1) l2_prefetch(&g_s.ar[0][0][0][0] + (cta & 63) * 128, 2048, POL_NORMAL);
        } else {
            unsigned long long u;
            uint32_t it = 0;
            do {
                spin_guard(it);
                asm volatile("ld.relaxed.gpu.global.b64 %0, [%1];" : "=l"(u) : "l"(&g_s.x2[wq * 32 + lane]) : "memory");
            } while (__any_sync(0xffffffffu, (uint32_t)(u >> 32) != tag - 1));
            xo = (uint32_t)u;
        }
        const uint32_t t16 = tag & 0xffffu;
        const uint4* src = &g_s.part[cta][wq][lane & 15][lane >> 4];
        const bool three = (lane & 15) == 0;
        if (wq == 0) {
            const uint32_t target = ((tag >> 2) * 2 + (TAIL ? 2 : 1)) * (2 * NCTA);
            uint32_t it = 0;
            while (true) {
                uint32_t v;
                asm volatile("ld.acquire.gpu.global.u32 %0, [%1];" : "=r"(v) : "l"(&g_s.done[0]) : "memory");
                const int rem = __shfl_sync(0xffffffffu, (int)(target - v), 0);
                if (rem <= 0) break;
                spin_guard(it);
                if (rem > 16) delay_cycles(400);
            }
        }
        __syncthreads();
        uint4 a = ll_ld_last(src), b = ll_ld_last(src + 32), e = make_uint4(0, 0xff800000u | t16, 0, t16);
        if (three) e = ll_ld_last(src + 64);
        const uint32_t wa0 = Z_WO + wq * 2048 + ((lane & 7) + (lane >> 4) * 8) * 128 + ((((lane >> 3) & 1) ^ (lane & 7)) << 4);
        uint32_t f0[4][4], f1[4][4];
        mbar_wait(TAIL ? SM_TBAR : SM_WBAR, TAIL ? 0 : 1);
        if (TAIL) {
#pragma unroll
            for (int mt = 0; mt < 4; mt++) {
                ldsm4t(f0[mt], wa0 ^ (mt << 5));
                ldsm4t(f1[mt], (wa0 ^ (mt << 5)) + USTR);
            }
        }
        {
            uint32_t it = 0;
            while (__any_sync(0xffffffffu, ((a.y ^ t16) | (a.w ^ t16) | (b.y ^ t16) | (b.w ^ t16) | (e.y ^ t16) | (e.w ^ t16)) << 16 != 0)) {
                spin_guard(it);
                a = ll_ld_last(src);
                b = ll_ld_last(src + 32);
                if (three) e = ll_ld_last(src + 64);
            }
        }
        if (!TAIL && wq >= 6) l2_prefetch((wq == 6 ? p.wu : p.wd) + (size_t)cta * 14336, 14336, POL_FIRST);
        const float la = __uint_as_float(__byte_perm(a.w, a.y, 0x7632)), lb = __uint_as_float(__byte_perm(b.w, b.y, 0x7632));
        const float le = __uint_as_float(__byte_perm(e.w, e.y, 0x7632));
        float mm;
        {
            int k = __float_as_int(fmaxf(fmaxf(la, lb), le));
            k ^= (k >> 31) & 0x7fffffff;
            k = __reduce_max_sync(0xffffffffu, k);
            k ^= (k >> 31) & 0x7fffffff;
            mm = __int_as_float(k);
        }
        const float wa = ex2(la - mm), wb = ex2(lb - mm), we = ex2(le - mm);
        const float v0 = fmaf(we, __uint_as_float(e.x), fmaf(wb, __uint_as_float(b.x), wa * __uint_as_float(a.x)));
        const float v1 = fmaf(we, __uint_as_float(e.z), fmaf(wb, __uint_as_float(b.z), wa * __uint_as_float(a.z)));
        float ws = wa + wb + we;
        float kk = (lane & 8) ? v1 : v0;
        kk += __shfl_xor_sync(0xffffffffu, (lane & 8) ? v0 : v1, 8);
        ws += __shfl_xor_sync(0xffffffffu, ws, 8);
        if (!TAIL) {
#pragma unroll
            for (int mt = 0; mt < 2; mt++) {
                ldsm4t(f0[mt], wa0 ^ (mt << 5));
                ldsm4t(f1[mt], (wa0 ^ (mt << 5)) + USTR);
            }
        }
#pragma unroll
        for (int k = 4; k > 0; k >>= 1) {
            kk += __shfl_xor_sync(0xffffffffu, kk, k);
            ws += __shfl_xor_sync(0xffffffffu, ws, k);
        }
        {
            float r; asm("rcp.approx.ftz.f32 %0, %1;" : "=f"(r) : "f"(ws));
            const uint32_t o = pack_bf16(kk * r, 0.f);
            if ((lane & 7) == 0) sts16(SM_RED + 128 + (wq & 3) * 16 + (wq >> 2) * 8 + ((lane >> 3) & 1) * 4 + (lane >> 4) * 2, o);
        }
        uint4* out = &g_s.ar[TAIL ? 2 : 0][cta & 1][wq * 16 + (lane >> 1)][lane & 1];
        __syncthreads();
        const uint4 ob = lds128(SM_RED + 128 + t * 16);
        float c0[4] = {0.f, 0.f, 0.f, 0.f}, c1[4] = {0.f, 0.f, 0.f, 0.f};
#pragma unroll
        for (int mt = 0; mt < 4; mt++) {
            constexpr int NP = TAIL ? 4 : 2;
            uint32_t* g0 = f0[mt % NP];
            uint32_t* g1 = f1[mt % NP];
            if (mt >= NP) {
                ldsm4t(g0, wa0 ^ (mt << 5));
                ldsm4t(g1, (wa0 ^ (mt << 5)) + USTR);
            }
            const bool mine = (g >> 1) == mt;
            mma(c0, g0, mine ? ob.x : 0u, mine ? ob.y : 0u);
            mma(c1, g1, mine ? ob.z : 0u, mine ? ob.w : 0u);
        }
        ar_add(out, c0[0] + c1[0], c0[2] + c1[2]);
        if (!TAIL) {
            if (wq == 4 || wq == 5) bar_sync(4, 256); else bar_arrive(4, 256);
        }
    }
#pragma unroll 1
    for (int hv = 0; hv < 2; hv++) {
        const int half = __shfl_sync(0xffffffffu, hv, 0);
        const bool ffn = cta < 112;
        if (TAIL && (half ? cta != 0 : !ffn)) break;
        uint32_t t0;
        asm volatile("mov.u32 %0, %%clock;" : "=r"(t0));
        const int lane = tid_now() & 31, g = lane >> 2, t = lane & 3;
        const bool qs = !TAIL && half;
        [[maybe_unused]] const int h = wq - 4;
        [[maybe_unused]] const uint32_t z = SM_SLOTS + h * USTR;
        if (!TAIL && (wq == 4 || wq == 5)) {
            if (!half) {
                if (ffn) load_ffn(tm, cta, h, z);
            } else if (!(ffn && h == 0)) {
                if (!ffn) delay_cycles(D_SKIP);
                load_wq(tm, cta, h, z);
            }
        }
        if (!TAIL && !half && wq >= 6) {
            delay_cycles(wq == 6 ? D_QP0 : D_QP1);
            l2_prefetch(p.wq + (size_t)(cta + (wq - 6) * 128) * 16384, 16384, POL_FIRST);
        }
        constexpr int NPRE = TAIL ? 4 : 2;
        uint32_t f[NPRE][8];
        const int row = (wq & 3) * 64 + (lane & 7) + (lane >> 4) * 8;
        const uint32_t a0 = qs ? SM_SLOTS + (wq >> 2) * USTR + row * 64 + ((((lane >> 3) & 1) ^ ((lane >> 1) & 3)) << 4)
                               : SM_WG + (wq >> 2) * 8192 + row * 32 + ((((lane >> 3) ^ (lane >> 2)) & 1) << 4);
        const uint32_t a1 = qs ? a0 ^ 32 : a0 - (SM_WG - Z_GU), kstride = qs ? 1024 : 512;
        {
            const uint4* src = &g_s.ar[(TAIL ? 2 : 0) + half][0][wq * 16 + (lane >> 1)][lane & 1];
            const uint32_t cnt = __float_as_uint(half ? 56.f : 64.f);
            if (TAIL && !half) {
                mbar_wait(SM_WBAR, 0);
#pragma unroll
                for (int ks = 0; ks < NPRE; ks++) {
                    ldsm4t(f[ks], a0 + ks * kstride);
                    ldsm4t(f[ks] + 4, a1 + ks * kstride);
                }
            }
            {
                const uint32_t d = (half && !ffn) ? D_AR + D_SKIP : D_AR;
                uint32_t t1;
                do { asm volatile("mov.u32 %0, %%clock;" : "=r"(t1)); } while (t1 - t0 < d);
            }
            uint4 u, v;
            uint32_t it = 0;
            do {
                spin_guard(it);
                u = ll_ld(src);
                v = ll_ld(src + 1024);
            } while (__any_sync(0xffffffffu, u.x != cnt || u.w != cnt || v.x != cnt || v.w != cnt));
            const uint32_t y = pack_bf16(__uint_as_float(u.y) + __uint_as_float(v.y), __uint_as_float(u.z) + __uint_as_float(v.z));
            xo = pack_bf16(bf_lo(xo) + bf_lo(y), bf_hi(xo) + bf_hi(y));
        }
        if (!half && !ffn) continue;
        const uint32_t xw = movm(xo);
        if (TAIL && half) {
            reinterpret_cast<uint32_t*>(p.out)[wq * 32 + lane] = xw;
            if (wq == 0) {
                if (lane < 16) g_s.ticket[lane >> 3][lane & 7][0] = 0;
                if (lane == 16) g_s.epoch = (tag >> 2) + 1;
            }
            break;
        }
        if (!TAIL) {
            mbar_wait(SM_WBAR, qs && ffn);
#pragma unroll
            for (int ks = 0; ks < NPRE; ks++) {
                ldsm4t(f[ks], a0 + ks * kstride);
                ldsm4t(f[ks] + 4, a1 + ks * kstride);
            }
        }
        ln_gemv_part<NPRE>(f, a0, a1, kstride, xw, wq, lane);
        const uint32_t wd0 = Z_GU + USTR + wq * 2048 + ((lane & 7) + (lane >> 4) * 8) * 128 + ((((lane >> 3) & 1) ^ (lane & 7)) << 4);
        uint32_t d[4][4];
        constexpr int DPRE = TAIL ? 4 : 0;
#pragma unroll
        for (int mt = 0; mt < DPRE; mt++) ldsm4t(d[mt], wd0 ^ (mt << 5));
        uint4* out = qs ? q_dst(p, 1, cta, lane) : &g_s.ar[TAIL ? 3 : 1][cta & 1][wq * 16 + (lane >> 1)][lane & 1];
        __syncthreads();
        if (!TAIL && !half && wq == 4) load_wq(tm, cta, 0, z);
        float r = ln_gemv_fin(lane);
        if (qs) {
            if (wq == 0) publish_q(out, r, tag, lane);
            if (cta == 0)
                asm volatile("st.relaxed.gpu.global.b64 [%0], %1;" ::"l"(&g_s.x2[wq * 32 + lane]), "l"((unsigned long long)tag << 32 | xo) : "memory");
            __syncthreads();
            break;
        }
        r = bf16r(r);
        const float up = __shfl_down_sync(0xffffffffu, r, 16);
#pragma unroll
        for (int mt = DPRE; mt < 4; mt++) ldsm4t(d[mt], wd0 ^ (mt << 5));
        const float hh = (r > 0.f ? r : 0.f * r) * up;
        const float h0 = __shfl_sync(0xffffffffu, hh, 2 * t), h1 = __shfl_sync(0xffffffffu, hh, 2 * t + 1);
        const float h2 = __shfl_sync(0xffffffffu, hh, 2 * t + 8), h3 = __shfl_sync(0xffffffffu, hh, 2 * t + 9);
        const uint32_t b0 = pack_bf16(h0, h1), b1 = pack_bf16(h2, h3);
        float c0[4] = {0.f, 0.f, 0.f, 0.f}, c1[4] = {0.f, 0.f, 0.f, 0.f};
#pragma unroll
        for (int mt = 0; mt < 4; mt++) {
            const bool mine = (g >> 1) == mt;
            mma((mt & 1) ? c1 : c0, d[mt], mine ? b0 : 0u, mine ? b1 : 0u);
        }
        ar_add(out, c0[0] + c1[0], c0[2] + c1[2]);
        if (!TAIL) {
            if (wq == 4 || wq == 5) bar_sync(4, 256); else bar_arrive(4, 256);
        }
    }
}

#define UVARS                                                                                               \
    const int wqu = __shfl_sync(0xffffffffu, tid_now() >> 5, 0);                                            \
    const int wg = wqu >> 2, wj = wqu & 3;                                                                  \
    [[maybe_unused]] const int head = unit_head(cta, wg), ui = unit_index(cta, wg), tb = head * NTILE;      \
    [[maybe_unused]] const uint32_t slots = SM_SLOTS + wg * USTR, bars = SM_BAR + wg * 48;                  \
    [[maybe_unused]] const int barid = 1 + wg;                                                              \
    [[maybe_unused]] const uint32_t qbase = cta < 128 ? SM_Q : SM_WG + wg * 1024;                           \
    [[maybe_unused]] const uint32_t rec = SM_ST + wg * 16;                                                  \
    [[maybe_unused]] const uint32_t mx = SM_MX + wg * 64;
#define Q_RD (qbase + (lane & 15) * 16)
#define P_RD (SM_P + wg * 512 + (lane & 15) * 16)
#define P_WR (SM_P + wg * 512 + (wj >> 1) * 256 + (wj & 1) * 8 + (lane & 15) * 16)

__device__ __forceinline__ void static_phase(const Maps& tm, const int cta, Acc& acc, uint32_t (*rp)[48]) {
    UVARS
#pragma unroll 1
    for (int rv = 0; rv < NSTAT; rv++) {
        const int rn = __shfl_sync(0xffffffffu, rv, 0);
        const int lane = tid_now() & 31;
        const uint32_t d = (uint32_t)(0x10210432105432ull >> (8 * rn)), par = 0x7c0u >> (2 * rn);
        const int sk = d & 7, sv = (d >> 4) & 7;
        Pack pk;
        pk.cmp = SM_CMP + wg * 16;
        pk.esc = SM_ESC + wg * (ECAP * 8);
        pk.key = (rn < 4 ? rn + 3 : 6 - rn) << 11 | wj << 5 | lane;
        const bool inplace = rn < 4;
        uint32_t dst = slots + 2 * SLOT + (6 - rn) * 24576 + (wj * 32 + lane) * 16;
        uint32_t kb = k_offset(slots, wj, lane) + sk * SLOT;
        float s[4] = {0.f, 0.f, 0.f, 0.f}, s2[4] = {0.f, 0.f, 0.f, 0.f};
        uint32_t a[16];
        mbar_wait(bars + sk * 8, par & 1);
        {
            const uint32_t b4 = lds32(pk.cmp);
#pragma unroll 1
            for (int hv = 0; hv < 2; hv++) {
                const int h = __shfl_sync(0xffffffffu, hv, 0);
                load_khalf(a, kb);
                pack16(a, b4, inplace ? kb : dst, inplace ? kb ^ 32 : dst + 2048, inplace ? kb ^ 64 : dst + 4096, h, pk);
                qk_half(s, s2, a, Q_RD + h * 512);
                kb += 8192; dst += 6144;
            }
        }
#pragma unroll
        for (int i = 0; i < 4; i++) s[i] += s2[i];
        softmax_step(s, acc, P_WR, mx, barid, lane, wj);
        if (rn >= 5 && wj == 1) tma_tile(rn == 5 ? &tm.v : &tm.k, tb + (rn + 1) * NUNIT + ui, slots + sk * SLOT, bars + sk * 8);
        __syncwarp();
        uint32_t vb = v_offset(slots, wj, lane) + sv * SLOT;
        mbar_wait(bars + sv * 8, (par >> 1) & 1);
        {
            const uint32_t b4 = lds32(pk.cmp + 4);
#pragma unroll 1
            for (int yv = 0; yv < 2; yv++) {
                const int y = __shfl_sync(0xffffffffu, yv, 0);
                load_vhalf(a, vb);
                pack16(a, b4, inplace ? vb : dst, inplace ? vb ^ 32 : dst + 2048, inplace ? vb + 2048 : dst + 4096, 2 + y, pk);
                pv_half<true>(acc, a, SM_P + wg * 512 + (tid_now() & 15) * 16 + y * 256);
                vb += 4096; dst += 6144;
            }
            vb -= 8192;
        }
        {
            const uint32_t kb2 = k_offset(slots, wj, tid_now() & 31) + sk * SLOT;
            if (rn == 0) park(rp[0], kb2, vb);
            if (rn == 1) park(rp[1], kb2, vb);
            if (rn == 2) park(rp[2], kb2, vb);
            if (rn == 3) park(rp[3], kb2, vb);
        }
        asm volatile("fence.proxy.async.shared::cta;" ::: "memory");
        bar_sync(barid + 9, 128);
        const int j = (int)((wj == 1 ? 0x00c0a86u : 0xf00b907u) >> (4 * rn)) & 15;
        if ((wj == 1 || wj == 2) && j) issue_item(j, tm, tb, ui, slots, bars);
        if (wj == 0) {
            const uint32_t st = lds32(rec + 4);
            if (lane == 0 && lds32(pk.cmp + 8) > ECAP) {
                sts16(SM_KEEP + wg * 64 + (st & 255) * 2, rn * NUNIT + ui);
                sts32(rec + 4, (st + 1) | 0x10000u << (pk.key >> 11));
            }
            __syncwarp();
        }
    }
    {
        uint32_t c = slots + 2 * SLOT + 12288 + (tid_now() & 127) * 16;
#pragma unroll 1
        for (int j = 0; j < 6; j++, c += 2048) {
            const uint4 u = lds128(c), v = lds128(c + 36864);
            sts128(c, v.x, v.y, v.z, v.w);
            sts128(c + 36864, u.x, u.y, u.z, u.w);
        }
        asm volatile("fence.proxy.async.shared::cta;" ::: "memory");
    }
    if (wqu == 0) __threadfence();
    bar_sync(barid + 9, 128);
}

__device__ __forceinline__ void acc_init(Acc& a) {
#pragma unroll
    for (int i = 0; i < 4; i++) { a.o[0][i] = 0.f; a.o[1][i] = 0.f; a.l[i] = 0.f; }
    a.m0 = a.m1 = __int_as_float(0xff800000);
}

__device__ __forceinline__ void attention_pass(const Maps& tm, const Params& p, const int cta, const int ph, const uint32_t tag0,
                                               Acc& acc, uint32_t (*rp)[48], float* s, const uint32_t allflags) {
    UVARS
    const int lim = ph ? T_KEEP0 : NTILE;
    uint32_t ticket = 0;
    if (wj == 0) draw_ticket(ticket, p, ph, head, tid_now() & 31);
    const uint32_t st0 = __shfl_sync(0xffffffffu, lds32(rec + 4), 0);
    uint32_t phbits = __shfl_sync(0xffffffffu, lds32(rec + 12), 0);
    int nk = st0 & 255;
    uint32_t cur = DESC(0, 1) | 256;
    uint32_t q0 = 0, q1 = 0;
    int rn = NSTAT, ki = 0, since = 1;
    bool open = true;
    if (ph) {
        rn = 0; q0 = DESC(0, 3) | 256; cur = DESC(2, 1) | 128;
        if (nk > 0 && __shfl_sync(0xffffffffu, (int)lds16(SM_KEEP + wg * 64 + nk * 2 - 2), 0) >= T_KEEP0) nk--;
        else cur |= 512;
    }
#pragma unroll 1
    while (true) {
        const int lane = tid_now() & 31;
        const int sk = cur & 7, sv = (cur >> 3) & 7;
        const bool keeps = ph && ki < nk && cur;
        const bool want = cur && open && (!(q0 & 256) || (keeps && since < 1));
        int tkeep = 0;
        if (keeps) tkeep = __shfl_sync(0xffffffffu, lds16(SM_KEEP + wg * 64 + ki * 2), 0);
        const bool resid = rn + (cur == 0) < NSTAT;
        if (cur ? !(cur & 512) : !(st0 >> (16 + rn) & 1)) {
            Pack pk;
            pk.cmp = SM_CMP + wg * 16;
            pk.esc = SM_ESC + wg * (ECAP * 8);
            pk.key = rn << 11 | wj << 5 | lane;
            uint32_t a[16], vb, flags = 0;
            if (cur) {
                vb = v_offset(slots, wj, lane) + sv * SLOT;
                if (!(cur & 128)) {
                    const uint32_t kb = k_offset(slots, wj, lane) + sk * SLOT;
                    float s2[4] = {0.f, 0.f, 0.f, 0.f};
                    s[0] = s[1] = s[2] = s[3] = 0.f;
                    mbar_wait(bars + sk * 8, (phbits >> sk) & 1);
                    load_khalf(a, kb);
                    qk_half(s, s2, a, Q_RD);
                    load_khalf(a, kb + 8192);
                    qk_half(s, s2, a, Q_RD + 512);
                    mbar_wait(bars + sv * 8, (phbits >> sv) & 1);
                    phbits ^= 1u << sk | 1u << sv;
#pragma unroll
                    for (int i = 0; i < 4; i++) s[i] += s2[i];
                }
                load_vhalf(a, vb);
            } else {
                vb = slots + 2 * SLOT + (wj * 32 + lane) * 16;
                flags = allflags >> (4 * rn);
                if (rn < 3) {
                    const uint4 u = lds128(((vb & ~32u) | (rn & 1) << 5) + 32768 + (rn >> 1) * 2048);
                    s[0] = __uint_as_float(u.x); s[1] = __uint_as_float(u.y); s[2] = __uint_as_float(u.z); s[3] = __uint_as_float(u.w);
                    vb += ((0x423 >> (4 * rn)) & 7) * 12288;
                } else {
                    vb += 49152;
                    if (rn == 3) unpark(rp[0], vb);
                    if (rn == 4) unpark(rp[1], vb);
                    if (rn == 5) unpark(rp[2], vb);
                    if (rn == 6) unpark(rp[3], vb);
                    const uint32_t up = lds32(pk.cmp);
                    float s2[4] = {0.f, 0.f, 0.f, 0.f};
                    s[0] = s[1] = s[2] = s[3] = 0.f;
#pragma unroll 1
                    for (int h = 0; h < 2; h++) {
                        unpack16(a, up, vb + h * 6144, h, flags, pk);
                        qk_half(s, s2, a, Q_RD + h * 512);
                    }
#pragma unroll
                    for (int i = 0; i < 4; i++) s[i] += s2[i];
                }
                unpack16(a, lds32(pk.cmp + 4), vb + 12288, 2, flags, pk);
            }
            softmax_step(s, acc, P_WR, mx, barid, lane, wj);
            pv_half<false>(acc, a, P_RD);
            if (cur) load_vhalf(a, vb + 4096);
            else unpack16(a, lds32(pk.cmp + 4), vb + 18432, 3, flags, pk);
            pv_half<false>(acc, a, P_RD + 256);
        } else {
            bar_sync(barid + 9, 128);
        }
        if (wj == 0)
            asm volatile("{\n.reg .pred p, q;\n.reg .u32 w;\nmov.u32 w, %6;\nsetp.eq.u32 p, %7, 0;\n@p bra.uni N_%=;\n"
                         "shfl.sync.idx.b32 w, %1, 0, 31, 0xffffffff;\nadd.u32 w, w, %5;\nmin.u32 w, w, %6;\nN_%=:\n"
                         "setp.eq.u32 p, %2, 0;\nsetp.ge.and.u32 q, w, %3, p;\n@q or.b32 w, w, 0x10000;\n"
                         "@p st.shared.u32 [%0], w;\n@q red.relaxed.gpu.global.add.u32 [%4], 1;\n}"
                         ::"r"(rec), "r"(ticket), "r"(lane), "r"((!resid && !q0 && !keeps) ? lim : NTILE + 1),
                           "l"(&g_s.done[lane]), "n"(T_DYN0 + NUNIT), "n"(NTILE), "r"((uint32_t)want) : "memory");
        bar_sync(8 + wg, 128);
        int tv = __shfl_sync(0xffffffffu, (int)lds32(rec), 0);
        if (tv > NTILE) break;
        if (cur == 0) rn++;
        uint32_t push = 0;
        const bool streamed = tv < lim;
        if (streamed) push = (cur & 127) | 256;
        else if (keeps) { tv = tkeep; push = cur & 127; }
        if (push && (wj == 1 || wj == 2)) {
            const int sl = wj == 1 ? sk : sv;
            tma_tile(wj == 1 ? &tm.k : &tm.v, tb + tv, slots + sl * SLOT, bars + sl * 8);
            if (!ph && tv >= T_KEEP0 && tv < T_KEEPEND) l2_prefetch((wj == 1 ? p.k : p.v) + (size_t)(tb + tv) * SLOT, SLOT, POL_NORMAL);
        }
        if (streamed) {
            since++;
            if (!ph && tv >= T_KEEP0) {
                if (wj == 3 && lane == 0) sts16(SM_KEEP + wg * 64 + nk * 2, tv);
                nk++;
                if (nk >= KEEPCAP) open = false;
            }
            if (open && wj == 0) draw_ticket(ticket, p, ph, head, lane);
        } else {
            if (want) open = false;
            if (keeps) { ki++; since = 0; }
        }
        if (q0) q1 |= push; else q0 = push;
        if (resid && (q0 == 0 || (streamed && q1 == 0))) {
            cur = 0;
        } else {
            cur = q0; q0 = q1; q1 = 0;
        }
    }
    const int lane = tid_now() & 31;
    {
        const int e = (lane >> 1) & 1;
        float l = e ? acc.l[1] : acc.l[0], m = e ? acc.m1 : acc.m0;
        float inv; asm("rcp.approx.ftz.f32 %0, %1;" : "=f"(inv) : "f"(l));
        float lg; asm("lg2.approx.ftz.f32 %0, %1;" : "=f"(lg) : "f"(l));
        uint32_t lam = __float_as_uint(m + lg);
        const uint32_t t16 = (tag0 + ph + 1) & 0xffffu;
        uint32_t ta = (lam & 0xffff0000u) | t16, tc = (lam << 16) | t16;
        uint4* dst = part_dst(p, head, ui, wqu * 32 + lane);
        ll_st(dst, __float_as_uint((e ? acc.o[0][1] : acc.o[0][0]) * inv), ta,
                   __float_as_uint((e ? acc.o[0][3] : acc.o[0][2]) * inv), tc);
        ll_st(dst + 4 * NUNIT * 2, __float_as_uint((e ? acc.o[1][1] : acc.o[1][0]) * inv), ta,
                                   __float_as_uint((e ? acc.o[1][3] : acc.o[1][2]) * inv), tc);
    }
    if (wj == 0 && lane == 0) {
        sts32(rec + 4, nk | (st0 & 0xffff0000u));
        sts32(rec + 12, phbits);
    }
}

__global__ void __launch_bounds__(256, 1)
fused_kernel(const __grid_constant__ Maps tm, const Params p) {
    extern __shared__ __align__(1024) unsigned char smem_raw[];
    const int cta = blockIdx.x;
    const bool worker = cta < 128;
    uint32_t tag0;
    if ((uint32_t)__cvta_generic_to_shared(smem_raw) != SM_BASE) __trap();
    uint32_t rp[4][48];
    Acc acc;
    {
        UVARS
        const int lane = tid_now() & 31;
        if (wj == 1 && worker) l2_prefetch(p.wq + (size_t)(cta * 2 + wg) * SLOT, SLOT, POL_NORMAL);
        if (wj == 0) {
#pragma unroll
            for (int i = 0; i < 6; i++) mbar_init(bars + i * 8, 1);
            mbar_init(SM_WBAR + wg * 8, 2);
            mbar_init(SM_DBAR + wg * 8, 1);
            asm volatile("fence.proxy.async.shared::cta;" ::: "memory");
            __syncwarp();
            if (worker && wg == 0) {
                load_wq(tm, cta, 0, SM_SLOTS + SLOT);
                load_wq(tm, cta, 1, SM_SLOTS + USTR + SLOT);
            }
            delay_cycles(D_KV);
            issue_item(0, tm, tb, ui, slots, bars);
            issue_item(1, tm, tb, ui, slots, bars);
            if (worker && wg == 0 && lane < 16) ll_st(q_dst(p, 0, cta, lane), 0, 0, 0, 0);
        }
        if (wj == 1) {
            if (lane < ECAP) sts64(SM_ESC + wg * (ECAP * 8) + lane * 8, 0xffffffffu, 0);
            if (lane < 2) sts128(rec + lane * 32, 0, 0, 0, 0x27);
        }
        if (wj == 2) {
            const uint4 u = *reinterpret_cast<const uint4*>(p.x + wg * 256 + lane * 8);
            sts128(SM_P + wg * 512 + lane * 16, u.x, u.y, u.z, u.w);
        }
        if (wqu == 7 && worker && lane < 16) ll_st(&g_s.ar[0][0][0][0] + (cta * 8 + (lane >> 1)) * 8 + (lane & 1), 0, 0, 0, 0);
        if (wqu == 3) {
            uint32_t e;
            asm volatile("ld.relaxed.gpu.global.u32 %0, [%1];" : "=r"(e) : "l"(&g_s.epoch) : "memory");
            sts32(SM_RED, e * 4 + 1);
        }
        __syncthreads();
        tag0 = __shfl_sync(0xffffffffu, lds32(SM_RED), 0);
        const uint32_t xw = lds32(SM_P + wqu * 128 + lane * 4);
        __syncthreads();
        uint32_t it = 0;
        int item = 2;
#pragma unroll 1
        for (int stage = worker ? 0 : 1; stage < 3 || item < 6;) {
            if (item < (stage ? 6 : 5) && (wj != 1 || stage == 3 || mbar_test(bars + item * 8, 0))) {
                if (wj == 1) issue_item(item, tm, tb, ui, slots, bars);
                item++;
                continue;
            }
            spin_guard(it);
            if (stage == 0) {
                if (!mbar_test(SM_WBAR, 0)) continue;
                const int row = wj * 64 + (lane & 7) + (lane >> 4) * 8;
                const uint32_t a0 = slots + SLOT + row * 64 + ((((lane >> 3) & 1) ^ ((lane >> 1) & 3)) << 4);
                uint32_t f[1][8];
                ldsm4t(f[0], a0);
                ldsm4t(f[0] + 4, a0 ^ 32);
                ln_gemv_part<1>(f, a0, a0 ^ 32, 1024, xw, wqu, lane);
                __syncthreads();
                if (wqu == 0) publish_q(q_dst(p, 0, cta, lane), ln_gemv_fin(lane), tag0, lane);
                if (wqu == 6 && cta < 112) {
                    expect_tx(SM_DBAR, SLOT);
                    tma_2d(&tm.wg, cta * 16, 0, SM_WG, SM_DBAR);
                    tma_2d(&tm.wg, cta * 16, 256, SM_WG + 8192, SM_DBAR);
                }
                __syncthreads();
            } else if (stage == 1) {
                if (!mbar_test(bars + 2 * 8, 0) || !mbar_test(bars + 3 * 8, 0)) continue;
#pragma unroll 1
                for (int h = 0; h < 4; h++) {
                    uint32_t r[16], m = 0;
                    load_khalf(r, k_offset(slots, wj, lane) + 2 * SLOT + h * 8192);
#pragma unroll
                    for (int j = 0; j < 16; j++) m = __vmaxu2(m, r[j] & 0x7fff7fffu);
                    m = __reduce_max_sync(0xffffffffu, max(m >> 23, (m >> 7) & 0xffu));
                    if (lane == 0)
                        asm volatile("red.shared.max.u32 [%0], %1;" ::"r"(SM_CMP + wg * 16 + (h & 2) * 2),
                                     "r"((min(max(m, 15u), 141u) + 112u) * 0x00800080u) : "memory");
                    __syncwarp();
                }
            } else {
                const uint4 v = ll_ld(&g_s.q[0][cta >> 7][head][wj * 32 + lane]);
                if (__any_sync(0xffffffffu, v.y != tag0 || v.w != tag0)) { delay_cycles(200); continue; }
                sts64(qbase + (wj * 32 + lane) * 8, v.x, v.z);
            }
            stage++;
        }
        bar_sync(barid + 9, 128);
#pragma unroll
        for (int i = 0; i < 4; i++)
#pragma unroll
            for (int j = 0; j < 48; j++) asm volatile("" : "=r"(rp[i][j]));
        acc_init(acc);
    }
    static_phase(tm, cta, acc, rp);
    float s[4] = {0.f, 0.f, 0.f, 0.f};
    uint32_t allflags = 0;
#pragma unroll 1
    for (int phv = 0;; phv = 1) {
        const int ph = __shfl_sync(0xffffffffu, phv, 0);
        attention_pass(tm, p, cta, ph, tag0, acc, rp, s, allflags);
        if (ph) break;
        uint32_t rx[32];
        {
            UVARS
            load_kfrag(rx, k_offset(slots, wj, tid_now() & 31));
            bar_sync(barid + 9, 128);
            if (worker && wj == 3) tma_rows(&tm.wo, cta * 32 + wg * 16, slots, SM_WBAR);
            if (cta < 112) mbar_wait(SM_DBAR, 0);
        }
        if (worker) gemv_chain<false>(tm, p, cta, tag0 + 1);
        UVARS
        const int lane = tid_now() & 31;
        const uint4* src = &g_s.q[1][cta >> 7][head][wj * 32 + lane];
        Pack pk = {SM_CMP + wg * 16, SM_ESC + wg * (ECAP * 8), (uint32_t)(wj << 5 | lane)};
        allflags = esc_flags(pk);
        uint4 v;
        uint32_t it = 0;
        do {
            spin_guard(it);
            if (it == 1 || !worker) delay_cycles(D_AG);
            v = ll_ld(src);
            if (it == 1 && wj == 1) tma_tile(&tm.k, tb + T_DYN0 + ui, slots, bars);
        } while (__any_sync(0xffffffffu, v.y != tag0 + 1 || v.w != tag0 + 1));
        sts64(qbase + (wj * 32 + lane) * 8, v.x, v.z);
        bar_sync(barid + 9, 128);
        float s2[4] = {0.f, 0.f, 0.f, 0.f};
        s[0] = s[1] = s[2] = s[3] = 0.f;
        qk_half(s, s2, rx, Q_RD);
        qk_half(s, s2, rx + 16, Q_RD + 512);
#pragma unroll
        for (int i = 0; i < 4; i++) s[i] += s2[i];
        {
            const uint32_t store = slots + 2 * SLOT + (wj * 32 + lane) * 16, up = lds32(pk.cmp);
#pragma unroll 1
            for (int pv = 2; pv >= 0; pv--) {
                const int pos = __shfl_sync(0xffffffffu, pv, 0), c = (0x120 >> (4 * pos)) & 3;
                pk.key = c << 11 | wj << 5 | lane;
                float z[4] = {0.f, 0.f, 0.f, 0.f}, z2[4] = {0.f, 0.f, 0.f, 0.f};
#pragma unroll 1
                for (int h = 0; h < 2; h++) {
                    uint32_t a[16];
                    const uint4 q0 = lds128(Q_RD + h * 512), q1 = lds128(Q_RD + h * 512 + 256);
                    unpack16(a, up, store + pos * 12288 + h * 6144, h, allflags >> (4 * c), pk);
                    mma(z, a, q0.x, q0.y);
                    mma(z2, a + 4, q0.z, q0.w);
                    mma(z, a + 8, q1.x, q1.y);
                    mma(z2, a + 12, q1.z, q1.w);
                }
                asm volatile("{\n.reg .pred p;\nsetp.eq.u32 p, %5, 0;\n@p st.shared.v4.f32 [%0], {%1,%2,%3,%4};\n}"
                             ::"r"(store + 32768 + (c >> 1) * 2048), "f"(z[0] + z2[0]), "f"(z[1] + z2[1]), "f"(z[2] + z2[2]),
                               "f"(z[3] + z2[3]), "r"(((lane >> 1) ^ c) & 1) : "memory");
                if (pos == 1) {
                    bar_sync(8 + wg, 128);
                    if (wj == 2) tma_tile(&tm.v, tb + T_DYN0 + ui, slots + 3 * SLOT, bars + 24);
                }
                __syncwarp();
            }
        }
        acc_init(acc);
    }
    if (worker) {
        UVARS
        if (wj == 3) tma_rows(&tm.wo, cta * 32 + wg * 16, slots + 2 * SLOT, SM_TBAR);
        if (wj == 2 && cta < 112) load_ffn(tm, cta, wg, slots + 3 * SLOT);
        gemv_chain<true>(tm, p, cta, tag0 + 2);
    }
}

typedef CUresult (*EncodeFn)(CUtensorMap*, CUtensorMapDataType, cuuint32_t, void*, const cuuint64_t*, const cuuint64_t*,
                             const cuuint32_t*, const cuuint32_t*, CUtensorMapInterleave, CUtensorMapSwizzle,
                             CUtensorMapL2promotion, CUtensorMapFloatOOBfill);

void make_map(EncodeFn encode, CUtensorMap* m, void* base, int rank, const cuuint64_t* gd, const cuuint64_t* gs,
              const cuuint32_t* bx, CUtensorMapSwizzle sw) {
    const cuuint32_t es[3] = {1, 1, 1};
    encode(m, CU_TENSOR_MAP_DATA_TYPE_BFLOAT16, rank, base, gd, gs, bx, es, CU_TENSOR_MAP_INTERLEAVE_NONE, sw,
           CU_TENSOR_MAP_L2_PROMOTION_NONE, CU_TENSOR_MAP_FLOAT_OOB_FILL_NONE);
}

}

extern "C" void kernel_launch(void* const* d_in, const int* in_sizes, int n_in, void* d_out, int out_size) {
    (void)in_sizes; (void)n_in; (void)out_size;
    static EncodeFn encode = nullptr;
    static void* scratch = nullptr;
    if (!encode) {
        void* fn = nullptr;
        cudaDriverEntryPointQueryResult qr;
        cudaGetDriverEntryPoint("cuTensorMapEncodeTiled", &fn, cudaEnableDefault, &qr);
        encode = (EncodeFn)fn;
        cudaGetSymbolAddress(&scratch, g_scratch);
        cudaFuncSetAttribute(fused_kernel, cudaFuncAttributeMaxDynamicSharedMemorySize, SM_TOTAL);
    }
    Maps tm;
    {
        const cuuint64_t gd[3] = {64, 8ull * 65536ull, 2}, gs[2] = {256, 128};
        const cuuint32_t bx[3] = {64, 64, 2};
        make_map(encode, &tm.k, d_in[1], 3, gd, gs, bx, CU_TENSOR_MAP_SWIZZLE_128B);
        make_map(encode, &tm.v, d_in[2], 3, gd, gs, bx, CU_TENSOR_MAP_SWIZZLE_128B);
    }
    {
        const cuuint64_t gd[2] = {4096, 512}, gs[1] = {8192};
        const cuuint32_t bx[2] = {32, 256};
        make_map(encode, &tm.wq, d_in[3], 2, gd, gs, bx, CU_TENSOR_MAP_SWIZZLE_64B);
    }
    {
        const cuuint64_t gd[3] = {64, 4096, 8}, gs[2] = {1024, 128};
        const cuuint32_t bx[3] = {64, 16, 8};
        make_map(encode, &tm.wo, d_in[4], 3, gd, gs, bx, CU_TENSOR_MAP_SWIZZLE_128B);
        const cuuint64_t gd2[3] = {64, 1792, 8};
        make_map(encode, &tm.wd, d_in[8], 3, gd2, gs, bx, CU_TENSOR_MAP_SWIZZLE_128B);
    }
    {
        const cuuint64_t gd[2] = {1792, 512}, gs[1] = {3584};
        const cuuint32_t bx[2] = {16, 256};
        make_map(encode, &tm.wg, d_in[6], 2, gd, gs, bx, CU_TENSOR_MAP_SWIZZLE_32B);
        make_map(encode, &tm.wu, d_in[7], 2, gd, gs, bx, CU_TENSOR_MAP_SWIZZLE_32B);
    }
    Params p;
    p.x = (const __nv_bfloat16*)d_in[0];
    p.k = (const char*)d_in[1];
    p.v = (const char*)d_in[2];
    p.wq = (const char*)d_in[3];
    p.wu = (const char*)d_in[7];
    p.wd = (const char*)d_in[8];
    p.out = (__nv_bfloat16*)d_out;
    p.s = (Scratch*)scratch;
    fused_kernel<<<NCTA, 256, SM_TOTAL, cudaStreamPerThread>>>(tm, p);
}
```

```cpp
#include <cuda_runtime.h>
#include <cuda_bf16.h>
#include <cuda.h>
#include <stdint.h>

namespace {

constexpr int NCTA      = 132;
constexpr int NUNIT     = 33;
constexpr int NTILE     = 1024;
constexpr int SLOT      = 16384;
constexpr int NSTAT     = 7;
constexpr int T_DYN0    = NSTAT * NUNIT;
#define NKEEP 200
#define KEEP_TAILSKIP 33
#define KRATIO 1
#define D_AR 650
#define D_SKIP 1500
#define WQ_EARLY 1
#define EARLY_K 1
#define D_QP0 1000
#define D_QP1 1600
#define OPTA 3
#define D_AG 100
#define D_KV 300
#define SUNROLL 1
#define MID_NPRE 2
#define S1_NPRE 2
#define MID_DPRE 0
#define ECAP 28
#define DBG_U 0
#define DBG_PH 0
constexpr int T_KEEP0   = NTILE - NKEEP;
constexpr int T_KEEPEND = NTILE - KEEP_TAILSKIP;
constexpr int SUNR      = SUNROLL;
constexpr int KEEPCAP   = 32;
constexpr unsigned SPIN_LIMIT = 1u << 22;

constexpr uint32_t SM_BASE  = 1024;
constexpr uint32_t USTR     = 2 * SLOT + 3 * 24576;
constexpr uint32_t SM_SLOTS = SM_BASE;
constexpr uint32_t SM_WG    = SM_SLOTS + 2 * USTR;
constexpr uint32_t SM_Q     = SM_WG + SLOT;
constexpr uint32_t SM_P     = SM_Q + 1024;
constexpr uint32_t SM_RED   = SM_P + 1024;
constexpr uint32_t SM_MX    = SM_RED;
constexpr uint32_t SM_BAR   = SM_RED + 192;
constexpr uint32_t SM_WBAR  = SM_BAR + 96;
constexpr uint32_t SM_TBAR  = SM_BAR + 104;
constexpr uint32_t SM_DBAR  = SM_BAR + 112;
constexpr uint32_t SM_KEEP  = SM_BAR + 128;
constexpr uint32_t SM_ST    = SM_KEEP + 128;
constexpr uint32_t SM_CMP   = SM_ST + 32;
constexpr uint32_t SM_ESC   = SM_CMP + 32;
constexpr int SM_TOTAL      = SM_ESC + 2 * ECAP * 8 - SM_BASE;
static_assert(SM_TOTAL <= 232448 && ECAP <= 32, "smem");

struct __align__(1024) Scratch {
    uint4 part[128][8][NUNIT][2];
    uint4 ar[4][2][128][8];
    uint2 x2[256];
    uint4 q[2][2][8][128];
    unsigned ticket[2][8][32];
    unsigned done[32];
    unsigned epoch;
};
__device__ Scratch g_scratch;
#define g_s (*p.s)
#define TS(i)
#define TSD(i)
#define TSW(i)
#define TT(ph, head, tile)

struct Maps { CUtensorMap k, v, wq, wo, wg, wu, wd; };
struct Params {
    const __nv_bfloat16* x;
    const char* k;
    const char* v;
    const char* wq;
    const char* wo;
    const char* wg;
    const char* wu;
    const char* wd;
    __nv_bfloat16* out;
    Scratch* s;
};

__device__ __forceinline__ void mbar_init(uint32_t bar, uint32_t cnt) {
    asm volatile("{\n.reg .pred p;\nelect.sync _|p, 0xffffffff;\n@p mbarrier.init.shared::cta.b64 [%0], %1;\n}" ::"r"(bar), "r"(cnt) : "memory");
}
__device__ __forceinline__ void mbar_wait(uint32_t bar, uint32_t parity) {
    asm volatile("{\n.reg .pred p, q;\n.reg .u32 c;\nmov.u32 c, 0;\n"
                 "W_%=:\nmbarrier.try_wait.parity.shared::cta.b64 p, [%0], %1;\nvote.sync.all.pred p, p, 0xffffffff;\n"
                 "@p bra.uni D_%=;\nadd.u32 c, c, 1;\nsetp.lt.u32 q, c, %2;\n@q bra.uni W_%=;\ntrap;\nD_%=:\n}"
                 ::"r"(bar), "r"(parity), "n"(SPIN_LIMIT) : "memory");
}
__device__ __forceinline__ void spin_guard(uint32_t& it) {
    asm volatile("{\n.reg .pred q;\nadd.u32 %0, %0, 1;\nsetp.gt.u32 q, %0, %1;\n@q trap;\n}" : "+r"(it) : "n"(SPIN_LIMIT));
}
constexpr uint64_t POL_FIRST = 0x12f0000000000000ull;
__device__ __forceinline__ void tma_rows(const CUtensorMap* tm, int row, uint32_t dst, uint32_t bar) {
    asm volatile("{\n.reg .pred p;\nelect.sync _|p, 0xffffffff;\n"
                 "@p mbarrier.arrive.expect_tx.shared::cta.b64 _, [%4], %6;\n"
                 "@p cp.async.bulk.tensor.3d.shared::cluster.global.mbarrier::complete_tx::bytes.L2::cache_hint "
                 "[%0], [%1, {%2, %3, %2}], [%4], %5;\n}"
                 ::"r"(dst), "l"(tm), "r"(0), "r"(row), "r"(bar), "l"(POL_FIRST), "r"(SLOT) : "memory");
}
__device__ __forceinline__ void tma_tile(const CUtensorMap* tm, int gtile, uint32_t dst, uint32_t bar) {
    tma_rows(tm, gtile * 64, dst, bar);
}
__device__ __forceinline__ void expect_tx(uint32_t bar, uint32_t bytes) {
    asm volatile("{\n.reg .pred p;\nelect.sync _|p, 0xffffffff;\n@p mbarrier.arrive.expect_tx.shared::cta.b64 _, [%0], %1;\n}"
                 ::"r"(bar), "r"(bytes) : "memory");
}
__device__ __forceinline__ void tma_2d(const CUtensorMap* tm, int c0, int c1, uint32_t dst, uint32_t bar) {
    asm volatile("{\n.reg .pred p;\nelect.sync _|p, 0xffffffff;\n"
                 "@p cp.async.bulk.tensor.2d.shared::cluster.global.mbarrier::complete_tx::bytes.L2::cache_hint "
                 "[%0], [%1, {%2, %3}], [%4], %5;\n}"
                 ::"r"(dst), "l"(tm), "r"(c0), "r"(c1), "r"(bar), "l"(POL_FIRST) : "memory");
}
__device__ __forceinline__ void l2_prefetch(const void* p, uint32_t bytes) {
    asm volatile("{\n.reg .pred p;\nelect.sync _|p, 0xffffffff;\n@p cp.async.bulk.prefetch.L2.global [%0], %1;\n}"
                 ::"l"(p), "r"(bytes) : "memory");
}
__device__ __forceinline__ void ldsm4(uint32_t* r, uint32_t a) {
    asm volatile("ldmatrix.sync.aligned.m8n8.x4.shared.b16 {%0,%1,%2,%3}, [%4];"
                 : "=r"(r[0]), "=r"(r[1]), "=r"(r[2]), "=r"(r[3]) : "r"(a) : "memory");
}
__device__ __forceinline__ void ldsm4t(uint32_t* r, uint32_t a) {
    asm volatile("ldmatrix.sync.aligned.m8n8.x4.trans.shared.b16 {%0,%1,%2,%3}, [%4];"
                 : "=r"(r[0]), "=r"(r[1]), "=r"(r[2]), "=r"(r[3]) : "r"(a) : "memory");
}
__device__ __forceinline__ void mma(float* c, const uint32_t* a, uint32_t b0, uint32_t b1) {
    asm volatile("mma.sync.aligned.m16n8k16.row.col.f32.bf16.bf16.f32 {%0,%1,%2,%3}, {%4,%5,%6,%7}, {%8,%9}, {%0,%1,%2,%3};"
                 : "+f"(c[0]), "+f"(c[1]), "+f"(c[2]), "+f"(c[3])
                 : "r"(a[0]), "r"(a[1]), "r"(a[2]), "r"(a[3]), "r"(b0), "r"(b1));
}
__device__ __forceinline__ uint32_t movm(uint32_t a) {
    uint32_t d; asm volatile("movmatrix.sync.aligned.m8n8.trans.b16 %0, %1;" : "=r"(d) : "r"(a)); return d;
}
__device__ __forceinline__ uint32_t pack_bf16(float lo, float hi) {
    uint32_t d; asm("cvt.rn.bf16x2.f32 %0, %1, %2;" : "=r"(d) : "f"(hi), "f"(lo)); return d;
}
__device__ __forceinline__ float bf16r(float v) { return __uint_as_float(pack_bf16(v, 0.f) << 16); }
__device__ __forceinline__ float bf_lo(uint32_t w) { return __uint_as_float(w << 16); }
__device__ __forceinline__ float bf_hi(uint32_t w) { return __uint_as_float(w & 0xffff0000u); }
__device__ __forceinline__ float ex2(float v) { float d; asm("ex2.approx.ftz.f32 %0, %1;" : "=f"(d) : "f"(v)); return d; }
__device__ __forceinline__ uint4 lds128(uint32_t a) {
    uint4 v; asm volatile("ld.shared.v4.u32 {%0,%1,%2,%3}, [%4];" : "=r"(v.x), "=r"(v.y), "=r"(v.z), "=r"(v.w) : "r"(a) : "memory"); return v;
}
__device__ __forceinline__ uint2 lds64(uint32_t a) {
    uint2 v; asm volatile("ld.shared.v2.u32 {%0,%1}, [%2];" : "=r"(v.x), "=r"(v.y) : "r"(a) : "memory"); return v;
}
__device__ __forceinline__ uint32_t lds32(uint32_t a) {
    uint32_t v; asm volatile("ld.shared.u32 %0, [%1];" : "=r"(v) : "r"(a) : "memory"); return v;
}
__device__ __forceinline__ void sts128(uint32_t a, uint32_t x, uint32_t y, uint32_t z, uint32_t w) {
    asm volatile("st.shared.v4.u32 [%0], {%1,%2,%3,%4};" ::"r"(a), "r"(x), "r"(y), "r"(z), "r"(w) : "memory");
}
__device__ __forceinline__ void sts64(uint32_t a, uint32_t x, uint32_t y) {
    asm volatile("st.shared.v2.u32 [%0], {%1,%2};" ::"r"(a), "r"(x), "r"(y) : "memory");
}
__device__ __forceinline__ void sts32(uint32_t a, uint32_t x) {
    asm volatile("st.shared.u32 [%0], %1;" ::"r"(a), "r"(x) : "memory");
}
__device__ __forceinline__ void sts16(uint32_t a, uint32_t x) {
    asm volatile("st.shared.u16 [%0], %1;" ::"r"(a), "h"((unsigned short)x) : "memory");
}
__device__ __forceinline__ uint32_t lds16(uint32_t a) {
    unsigned short v; asm volatile("ld.shared.u16 %0, [%1];" : "=h"(v) : "r"(a) : "memory"); return v;
}
__device__ __forceinline__ bool wg_bar_or(int id, bool p) {
    uint32_t r;
    asm volatile("{\n.reg .pred a, b;\nsetp.ne.u32 a, %2, 0;\nbar.red.or.pred b, %1, 128, a;\nselp.u32 %0, 1, 0, b;\n}"
                 : "=r"(r) : "r"(id), "r"((uint32_t)p) : "memory");
    return r != 0;
}
__device__ __forceinline__ uint4 ll_ld(const uint4* p) {
    unsigned long long a, b;
    asm volatile("ld.relaxed.gpu.global.v2.b64 {%0,%1}, [%2];" : "=l"(a), "=l"(b) : "l"(p) : "memory");
    return make_uint4((uint32_t)a, (uint32_t)(a >> 32), (uint32_t)b, (uint32_t)(b >> 32));
}
__device__ __forceinline__ void ll_st(uint4* p, uint32_t v0, uint32_t t0, uint32_t v1, uint32_t t1) {
    unsigned long long a = ((unsigned long long)t0 << 32) | v0, b = ((unsigned long long)t1 << 32) | v1;
    asm volatile("st.relaxed.gpu.global.v2.b64 [%0], {%1,%2};" ::"l"(p), "l"(a), "l"(b) : "memory");
}
__device__ __forceinline__ uint4 ll_ld_last(const uint4* p) {
    unsigned long long a, b;
    asm volatile("ld.relaxed.gpu.global.L2::cache_hint.v2.b64 {%0,%1}, [%2], %3;" : "=l"(a), "=l"(b) : "l"(p), "l"(POL_FIRST) : "memory");
    return make_uint4((uint32_t)a, (uint32_t)(a >> 32), (uint32_t)b, (uint32_t)(b >> 32));
}
__device__ __forceinline__ void bar_sync(int id, int n) { asm volatile("bar.sync %0, %1;" ::"r"(id), "r"(n) : "memory"); }
__device__ __forceinline__ void bar_arrive(int id, int n) { asm volatile("bar.arrive %0, %1;" ::"r"(id), "r"(n) : "memory"); }
__device__ __forceinline__ void delay_cycles(int n) {
    if (n > 0) {
        uint32_t t0, t1;
        asm volatile("mov.u32 %0, %%clock;" : "=r"(t0));
        do { asm volatile("mov.u32 %0, %%clock;" : "=r"(t1)); } while (t1 - t0 < (uint32_t)n);
    }
}
__device__ __forceinline__ int tid_now() {
    int t; asm volatile("mov.u32 %0, %%tid.x;" : "=r"(t)); return t;
}
__device__ __forceinline__ bool mbar_test(uint32_t bar, uint32_t parity) {
    uint32_t ok;
    asm volatile("{\n.reg .pred p;\nmbarrier.test_wait.parity.shared::cta.b64 p, [%1], %2;\nselp.u32 %0, 1, 0, p;\n}"
                 : "=r"(ok) : "r"(bar), "r"(parity) : "memory");
    return ok != 0;
}

struct Acc {
    float o[2][4];
    float l[4];
    float m0, m1;
};

constexpr float SCALE_LOG2 = 0.08838834764831845f * 1.4426950408889634f;

__device__ __forceinline__ void softmax_step(float* s, Acc& a, uint32_t p_wr, uint32_t mx, int barid, int lane, int wj) {
#pragma unroll
    for (int i = 0; i < 4; i++) s[i] *= SCALE_LOG2;
    bool over = fmaxf(s[0], s[2]) > a.m0 || fmaxf(s[1], s[3]) > a.m1;
    {
        uint32_t b0 = movm(pack_bf16(ex2(s[0] - a.m0), ex2(s[1] - a.m1)));
        uint32_t b1 = movm(pack_bf16(ex2(s[2] - a.m0), ex2(s[3] - a.m1)));
        if (lane < 16) sts64(p_wr, b0, b1);
    }
    if (__any_sync(0xffffffffu, wg_bar_or(barid, over))) {
        float x0 = fmaxf(s[0], s[2]), x1 = fmaxf(s[1], s[3]);
#pragma unroll
        for (int d = 4; d < 32; d <<= 1) {
            x0 = fmaxf(x0, __shfl_xor_sync(0xffffffffu, x0, d));
            x1 = fmaxf(x1, __shfl_xor_sync(0xffffffffu, x1, d));
        }
        if (lane < 2) sts64(mx + wj * 16 + lane * 8, __float_as_uint(x0), __float_as_uint(x1));
        bar_sync(barid + 9, 128);
        float n0 = a.m0, n1 = a.m1;
#pragma unroll
        for (int j = 0; j < 4; j++) {
            uint2 v = lds64(mx + j * 16 + (lane & 1) * 8);
            n0 = fmaxf(n0, __uint_as_float(v.x));
            n1 = fmaxf(n1, __uint_as_float(v.y));
        }
        float f0 = ex2(a.m0 - n0), f1 = ex2(a.m1 - n1);
        a.m0 = n0; a.m1 = n1;
        a.o[0][0] *= f0; a.o[0][2] *= f0; a.o[1][0] *= f0; a.o[1][2] *= f0; a.l[0] *= f0; a.l[2] *= f0;
        a.o[0][1] *= f1; a.o[0][3] *= f1; a.o[1][1] *= f1; a.o[1][3] *= f1; a.l[1] *= f1; a.l[3] *= f1;
        uint32_t b0 = movm(pack_bf16(ex2(s[0] - n0), ex2(s[1] - n1)));
        uint32_t b1 = movm(pack_bf16(ex2(s[2] - n0), ex2(s[3] - n1)));
        if (lane < 16) sts64(p_wr, b0, b1);
        bar_sync(barid + 9, 128);
    }
}

__device__ __forceinline__ uint32_t mul2(uint32_t a, uint32_t b) {
    uint32_t d; asm("mul.rn.bf16x2 %0, %1, %2;" : "=r"(d) : "r"(a), "r"(b)); return d;
}
__device__ __forceinline__ uint32_t fma2(uint32_t a, uint32_t b, uint32_t c) {
    uint32_t d; asm("fma.rn.bf16x2 %0, %1, %2, %3;" : "=r"(d) : "r"(a), "r"(b), "r"(c)); return d;
}
struct Pack {
    uint32_t cmp;
    uint32_t esc;
    uint32_t key;
};
__device__ __forceinline__ void pack16(const uint32_t* a, uint32_t up, uint32_t d0, uint32_t d1, uint32_t d2, int it,
                                       const Pack& pk) {
    const uint32_t dn = 0x7f007f00u - up, nup = up | 0x80008000u;
    uint32_t l[8], n[4], bad = 0;
#pragma unroll
    for (int g = 0; g < 4; g++) {
        uint32_t z[4], e = 0;
#pragma unroll
        for (int j = 0; j < 4; j++) {
            z[j] = mul2(a[4 * g + j], dn);
            e |= fma2(z[j], nup, a[4 * g + j]);
        }
        const uint32_t x0 = __byte_perm(z[0], z[1], 0x7531), x1 = __byte_perm(z[2], z[3], 0x7531);
        l[2 * g] = __byte_perm(z[0], z[1], 0x6420);
        e |= (x0 | x1) & 0x78787878u;
        l[2 * g + 1] = __byte_perm(z[2], z[3], 0x6420) | e;
        n[g] = x0 | __funnelshift_l(x1, x1, 4);
        if (e) bad |= 1u << g;
        if (g & 1) sts128(g == 1 ? d0 : d1, l[2 * g - 2], l[2 * g - 1], l[2 * g], l[2 * g + 1]);
    }
    sts128(d2, n[0], n[1], n[2], n[3]);
    if (bad) {
        uint32_t i;
        asm volatile("atom.shared.add.u32 %0, [%1], %2;" : "=r"(i) : "r"(pk.cmp + 8 + (d2 >> 31)), "r"(__popc(bad)) : "memory");
#pragma unroll
        for (int g = 0; g < 4; g++) {
            asm volatile("{\n.reg .pred p, q;\n.reg .u32 a;\nsetp.ne.u32 p, %1, 0;\nsetp.lt.and.u32 q, %0, %5, p;\n"
                         "@p st.shared.v2.u32 [%6], {%7, %8};\n@p st.shared.u32 [%9], %10;\nmad.lo.u32 a, %0, 8, %2;\n"
                         "@q st.shared.v2.u32 [a], {%3, %4};\n@p add.u32 %0, %0, 1;\n}"
                         : "+r"(i)
                         : "r"(bad & (1u << g)), "r"(pk.esc), "r"(pk.key | it << 9 | g << 7), "r"(a[4 * g + 3]),
                           "n"(ECAP), "r"((g < 2 ? d0 : d1) + (g & 1) * 8), "r"(a[4 * g]), "r"(a[4 * g + 1]), "r"(d2 + g * 4),
                           "r"(a[4 * g + 2]) : "memory");
        }
    }
    __syncwarp();
}
__device__ __forceinline__ uint32_t esc_flags(const Pack& pk) {
    const uint32_t e = lds32(pk.esc + min(pk.key & 31u, ECAP - 1u) * 8);
    return __reduce_or_sync(0xffffffffu, ((e ^ pk.key) & ~0x3f9fu) == 0 ? 1u << ((e >> 9) & 31) : 0u);
}
__device__ __forceinline__ void unpack16(uint32_t* a, uint32_t up, uint32_t c, int it, uint32_t flags, const Pack& pk) {
    const uint4 nn = lds128(c + 4096);
    const uint4 l0 = lds128(c), l1 = lds128(c + 2048);
    const uint32_t n[4] = {nn.x, nn.y, nn.z, nn.w};
    const uint32_t l[8] = {l0.x, l0.y, l0.z, l0.w, l1.x, l1.y, l1.z, l1.w};
#pragma unroll
    for (int g = 0; g < 4; g++) {
        const uint32_t h0 = n[g] & 0x87878787u, h1 = __funnelshift_r(n[g], n[g], 4) & 0x87878787u;
        a[4 * g]     = mul2(__byte_perm(l[2 * g], h0, 0x5140), up);
        a[4 * g + 1] = mul2(__byte_perm(l[2 * g], h0, 0x7362), up);
        a[4 * g + 2] = mul2(__byte_perm(l[2 * g + 1], h1, 0x5140), up);
        a[4 * g + 3] = mul2(__byte_perm(l[2 * g + 1], h1, 0x7362), up);
    }
    if (flags >> it & 1) {
        const uint32_t me = pk.key | it << 9;
        const uint2 e = lds64(pk.esc + min(me & 31u, ECAP - 1u) * 8);
        uint32_t hit = __ballot_sync(0xffffffffu, ((e.x ^ me) & ~0x19fu) == 0) & (uint32_t)((1ull << ECAP) - 1);
#pragma unroll 1
        while (hit) {
            const int src = __ffs(hit) - 1;
            hit &= hit - 1;
            const uint32_t d = __shfl_sync(0xffffffffu, e.x, src) ^ me, v = __shfl_sync(0xffffffffu, e.y, src);
#pragma unroll
            for (int g = 0; g < 4; g++)
                asm volatile("{\n.reg .pred p;\nsetp.eq.u32 p, %4, %5;\n@p ld.shared.v2.u32 {%0, %1}, [%6];\n"
                             "@p ld.shared.u32 %2, [%7];\n@p mov.u32 %3, %8;\n}"
                             : "+r"(a[4 * g]), "+r"(a[4 * g + 1]), "+r"(a[4 * g + 2]), "+r"(a[4 * g + 3])
                             : "r"(d), "r"(g << 7), "r"(c + (g >> 1) * 2048 + (g & 1) * 8), "r"(c + 4096 + g * 4), "r"(v) : "memory");
        }
    }
}

__device__ __forceinline__ void qk_half(float* s, float* s2, const uint32_t* a, uint32_t q) {
    const uint4 q0 = lds128(q), q1 = lds128(q + 256);
    mma(s, a, q0.x, q0.y);
    mma(s2, a + 4, q0.z, q0.w);
    mma(s, a + 8, q1.x, q1.y);
    mma(s2, a + 12, q1.z, q1.w);
}
__device__ __forceinline__ void mma_ones(float* c, uint32_t b) {
    asm volatile("mma.sync.aligned.m16n8k8.row.col.f32.bf16.bf16.f32 {%0,%1,%2,%3}, {%4,%4}, {%5}, {%0,%1,%2,%3};"
                 : "+f"(c[0]), "+f"(c[1]), "+f"(c[2]), "+f"(c[3]) : "r"(0x3f803f80u), "r"(b));
}
template <bool SMALL>
__device__ __forceinline__ void pv_half(Acc& a, const uint32_t* f, uint32_t pa) {
    const uint32_t ones[4] = {0x3f803f80u, 0x3f803f80u, 0x3f803f80u, 0x3f803f80u};
    const uint4 pp = lds128(pa);
    mma(a.o[0], f, pp.x, pp.y);
    mma(a.o[1], f + 4, pp.x, pp.y);
    if (SMALL) { mma_ones(a.l, pp.x); mma_ones(a.l, pp.y); } else mma(a.l, ones, pp.x, pp.y);
    mma(a.o[0], f + 8, pp.z, pp.w);
    mma(a.o[1], f + 12, pp.z, pp.w);
    if (SMALL) { mma_ones(a.l, pp.z); mma_ones(a.l, pp.w); } else mma(a.l, ones, pp.z, pp.w);
}
__device__ __forceinline__ void load_khalf(uint32_t* a, uint32_t k) {
#pragma unroll
    for (int j = 0; j < 4; j++) ldsm4(a + j * 4, k ^ (j << 5));
    __syncwarp();
}
__device__ __forceinline__ void load_vhalf(uint32_t* f, uint32_t v) {
    ldsm4t(f, v);
    ldsm4t(f + 4, v ^ 32);
    ldsm4t(f + 8, v + 2048);
    ldsm4t(f + 12, (v ^ 32) + 2048);
    __syncwarp();
}
__device__ __forceinline__ void park(uint32_t* r, uint32_t kb, uint32_t vb) {
#pragma unroll
    for (int j = 0; j < 12; j++) {
        const int it = j / 3, c = j % 3;
        const uint32_t ad = it < 2 ? (kb ^ (c << 5)) + it * 8192 : (vb ^ ((c & 1) << 5)) + (c >> 1) * 2048 + (it - 2) * 4096;
        const uint4 u = lds128(ad);
        r[4 * j] = u.x; r[4 * j + 1] = u.y; r[4 * j + 2] = u.z; r[4 * j + 3] = u.w;
    }
}
__device__ __forceinline__ void unpark(const uint32_t* r, uint32_t c) {
#pragma unroll
    for (int j = 0; j < 12; j++) sts128(c + j * 2048, r[4 * j], r[4 * j + 1], r[4 * j + 2], r[4 * j + 3]);
}
__device__ __forceinline__ uint32_t k_offset(uint32_t slots, int wj, int lane) {
    const int row = wj * 16 + (lane & 7) + ((lane >> 3) & 1) * 8;
    return slots + row * 128 + (((lane >> 4) ^ (row & 7)) << 4);
}
__device__ __forceinline__ uint32_t v_offset(uint32_t slots, int wj, int lane) {
    const int key = (lane & 7) + (lane >> 4) * 8, cg = wj * 4 + ((lane >> 3) & 1);
    return slots + (cg >> 3) * 8192 + key * 128 + (((cg & 7) ^ (key & 7)) << 4);
}
__device__ __forceinline__ void load_kfrag(uint32_t* rk, uint32_t kb) {
#pragma unroll
    for (int ks = 0; ks < 8; ks++) ldsm4(rk + ks * 4, (kb ^ ((ks & 3) << 5)) + (ks >> 2) * 8192);
}

template <int NPRE>
__device__ __forceinline__ void ln_gemv_part(uint32_t (*f)[8], uint32_t a0, uint32_t a1, uint32_t kstride, uint32_t xw,
                                             int wq, int lane) {
    const int t = lane & 3, g = lane >> 2;
    float c0[4] = {0.f, 0.f, 0.f, 0.f}, c1[4] = {0.f, 0.f, 0.f, 0.f};
#pragma unroll
    for (int ks = 0; ks < 4; ks++) {
        uint32_t* ff = f[ks % NPRE];
        if (ks >= NPRE) {
            ldsm4t(ff, a0 + ks * kstride);
            ldsm4t(ff + 4, a1 + ks * kstride);
        }
        uint32_t xa = __shfl_sync(0xffffffffu, xw, ks * 8 + t), xb = __shfl_sync(0xffffffffu, xw, ks * 8 + 4 + t);
        if (g & 1) xa = xb = 0x3f803f80u;
        mma(c0, ff, xa, xb);
        mma(c1, ff + 4, xa, xb);
    }
    {
        const float a = bf_lo(xw), b = bf_hi(xw);
        const float su = a + b, sq = fmaf(a, a, b * b);
        float keep = (lane & 16) ? sq : su, send = (lane & 16) ? su : sq;
        keep += __shfl_xor_sync(0xffffffffu, send, 16);
#pragma unroll
        for (int k = 8; k > 0; k >>= 1) keep += __shfl_xor_sync(0xffffffffu, keep, k);
        if ((lane & 15) == 0) sts32(SM_RED + (lane >> 4) * 32 + wq * 4, __float_as_uint(keep));
    }
    float y = (t & 2) ? ((t & 1) ? c1[2] : c1[0]) : ((t & 1) ? c0[2] : c0[0]);
    float z = (t & 2) ? ((t & 1) ? c1[3] : c1[1]) : ((t & 1) ? c0[3] : c0[1]);
    sts64(SM_Q + wq * 256 + (t * 8 + g) * 8, __float_as_uint(y), __float_as_uint(z));
}
__device__ __forceinline__ float sum4(uint4 u) {
    return (__uint_as_float(u.x) + __uint_as_float(u.y)) + (__uint_as_float(u.z) + __uint_as_float(u.w));
}
__device__ __forceinline__ float ln_gemv_fin(int lane) {
    float mean, rstd;
    {
        const uint4 a = lds128(SM_RED), b = lds128(SM_RED + 16), c = lds128(SM_RED + 32), d = lds128(SM_RED + 48);
        mean = (sum4(a) + sum4(b)) * (1.f / 512.f);
        const float var = fmaxf(fmaf(sum4(c) + sum4(d), 1.f / 512.f, -mean * mean), 0.f) + 1e-5f;
        asm("rsqrt.approx.ftz.f32 %0, %1;" : "=f"(rstd) : "f"(var));
    }
    uint2 u[8];
#pragma unroll
    for (int j = 0; j < 8; j++) u[j] = lds64(SM_Q + j * 256 + lane * 8);
#define S8(f) (((__uint_as_float(u[0].f) + __uint_as_float(u[1].f)) + (__uint_as_float(u[2].f) + __uint_as_float(u[3].f))) + \
               ((__uint_as_float(u[4].f) + __uint_as_float(u[5].f)) + (__uint_as_float(u[6].f) + __uint_as_float(u[7].f))))
    return (S8(x) - mean * S8(y)) * rstd;
#undef S8
}
__device__ __forceinline__ void ar_add(uint4* dst, float y0, float y1) {
    asm volatile("red.relaxed.gpu.global.add.v4.f32 [%0], {%1, %2, %3, %1};" ::"l"(dst), "f"(1.f), "f"(y0), "f"(y1) : "memory");
}

__device__ __forceinline__ int unit_head(int cta, int wg) { return cta < 128 ? ((cta + (cta >> 3)) & 7) : (cta - 128) * 2 + wg; }
__device__ __forceinline__ int unit_index(int cta, int wg) { return cta < 128 ? (cta >> 3) * 2 + wg : 32; }
__device__ __forceinline__ void issue_item(int j, const Maps& tm, int tb, int ui, uint32_t slots, uint32_t bars) {
    const int slot = (int)((0x1010210432105432ull >> (4 * j)) & 15);
    tma_tile((j & 1) ? &tm.v : &tm.k, tb + (j >> 1) * NUNIT + ui, slots + slot * SLOT, bars + slot * 8);
}
__device__ __forceinline__ void load_ffn(const Maps& tm, int cta, int h, uint32_t z) {
    if (h) {
        tma_rows(&tm.wd, cta * 16, z, (OPTA & 2) ? SM_DBAR + 8 : SM_WBAR);
    } else {
        expect_tx(SM_WBAR, SLOT);
        if (OPTA & 2) expect_tx(SM_WBAR, 0);
        tma_2d(&tm.wu, cta * 16, 0, z, SM_WBAR);
        tma_2d(&tm.wu, cta * 16, 256, z + 8192, SM_WBAR);
    }
}
__device__ __forceinline__ void load_wq(const Maps& tm, int cta, int h, uint32_t z) {
    expect_tx(SM_WBAR, SLOT);
    tma_2d(&tm.wq, cta * 32, h * 256, z, SM_WBAR);
}
__device__ __forceinline__ void draw_ticket(uint32_t& ticket, const Params& p, int ph, int head, int lane) {
    asm volatile("{\n.reg .pred p;\nsetp.eq.u32 p, %2, 0;\n@p atom.relaxed.gpu.global.inc.u32 %0, [%1], 0xfffffffe;\n}"
                 : "+r"(ticket) : "l"(&g_s.ticket[ph][head][0]), "r"(lane) : "memory");
}
#define DESC(sk, sv) ((uint32_t)((sk) | ((sv) << 3) | 64))

__device__ __forceinline__ uint4* part_dst(const Params& p, int head, int ui, int tid) {
    const int lane = tid & 31, g = lane >> 2, t = lane & 3;
    return &g_s.part[(head * 4 + 2 * (t & 1) + (t >> 1)) * 4 + ((tid >> 5) & 3)][g >> 1][ui][g & 1];
}
__device__ __forceinline__ uint4* q_dst(const Params& p, int layer, int cta, int lane) {
    return &g_s.q[layer][(lane >> 3) & 1][cta >> 4][((cta & 3) * 16 + ((cta >> 2) & 3) * 4) * 2 + (lane & 7)];
}
__device__ __forceinline__ void publish_q(uint4* out, float r, uint32_t tag, int lane) {
    const int src = (lane & 1) * 16 + ((lane >> 1) & 3) * 2;
    const float q0 = __shfl_sync(0xffffffffu, r, src), q1 = __shfl_sync(0xffffffffu, r, src + 1);
    const float q2 = __shfl_sync(0xffffffffu, r, src + 8), q3 = __shfl_sync(0xffffffffu, r, src + 9);
    if (lane < 16) ll_st(out, pack_bf16(q0, q1), tag, pack_bf16(q2, q3), tag);
}

template <bool TAIL>
__device__ __forceinline__ void gemv_chain(const Maps& tm, const Params& p, const int cta, const uint32_t tag) {
    constexpr uint32_t Z_WO = SM_SLOTS + (TAIL ? 2 : 0) * SLOT, Z_GU = SM_SLOTS + (TAIL ? 3 : 0) * SLOT;
    [[maybe_unused]] constexpr int TB = TAIL ? 16 : 0;
    const int wq = __shfl_sync(0xffffffffu, tid_now() >> 5, 0);
    uint32_t xo;
    {
        const int lane = tid_now() & 31, g = lane >> 2, t = lane & 3;
        if (!TAIL) {
            const unsigned short* xp = reinterpret_cast<const unsigned short*>(p.x) + wq * 64 + t * 16 + g;
            xo = xp[0] | (uint32_t)xp[8] << 16;
            if (wq >= 1 && wq < 4) asm volatile("prefetch.tensormap [%0];" ::"l"(wq == 1 ? &tm.wq : wq == 2 ? &tm.wu : &tm.wd) : "memory");
            if (wq == 1) l2_prefetch(&g_s.ar[0][0][0][0] + (cta & 63) * 128, 2048);
        } else {
            unsigned long long u;
            uint32_t it = 0;
            do {
                spin_guard(it);
                asm volatile("ld.relaxed.gpu.global.b64 %0, [%1];" : "=l"(u) : "l"(&g_s.x2[wq * 32 + lane]) : "memory");
            } while (__any_sync(0xffffffffu, (uint32_t)(u >> 32) != tag - 1));
            xo = (uint32_t)u;
        }
        const uint32_t t16 = tag & 0xffffu;
        const uint4* src = &g_s.part[cta][wq][lane & 15][lane >> 4];
        const bool three = (lane & 15) == 0;
        if (wq == 0) {
            const uint32_t target = ((tag >> 2) * 2 + (TAIL ? 2 : 1)) * (2 * NCTA);
            uint32_t it = 0;
            while (true) {
                uint32_t v;
                asm volatile("ld.acquire.gpu.global.u32 %0, [%1];" : "=r"(v) : "l"(&g_s.done[0]) : "memory");
                const int rem = __shfl_sync(0xffffffffu, (int)(target - v), 0);
                if (rem <= 0) break;
                spin_guard(it);
                if (rem > 16) delay_cycles(400);
            }
        }
        __syncthreads();
        TS(TB + 14);
        uint4 a = ll_ld_last(src), b = ll_ld_last(src + 32), e = make_uint4(0, 0xff800000u | t16, 0, t16);
        if (three) e = ll_ld_last(src + 64);
        const uint32_t wa0 = Z_WO + wq * 2048 + ((lane & 7) + (lane >> 4) * 8) * 128 + ((((lane >> 3) & 1) ^ (lane & 7)) << 4);
        uint32_t f0[4][4], f1[4][4];
        if (TAIL || !(OPTA & 1)) mbar_wait(TAIL ? SM_TBAR : SM_WBAR, TAIL ? 0 : 1);
        if (TAIL) {
#pragma unroll
            for (int mt = 0; mt < 4; mt++) {
                ldsm4t(f0[mt], wa0 ^ (mt << 5));
                ldsm4t(f1[mt], (wa0 ^ (mt << 5)) + USTR);
            }
        }
        {
            uint32_t it = 0;
            while (__any_sync(0xffffffffu, ((a.y ^ t16) | (a.w ^ t16) | (b.y ^ t16) | (b.w ^ t16) | (e.y ^ t16) | (e.w ^ t16)) << 16 != 0)) {
                spin_guard(it);
                a = ll_ld_last(src);
                b = ll_ld_last(src + 32);
                if (three) e = ll_ld_last(src + 64);
            }
        }
        TS(TB + 0);
        if (!TAIL && wq >= 6) l2_prefetch((wq == 6 ? p.wu : p.wd) + (size_t)cta * 14336, 14336);
        const float la = __uint_as_float(__byte_perm(a.w, a.y, 0x7632)), lb = __uint_as_float(__byte_perm(b.w, b.y, 0x7632));
        const float le = __uint_as_float(__byte_perm(e.w, e.y, 0x7632));
        float mm;
        {
            int k = __float_as_int(fmaxf(fmaxf(la, lb), le));
            k ^= (k >> 31) & 0x7fffffff;
            k = __reduce_max_sync(0xffffffffu, k);
            k ^= (k >> 31) & 0x7fffffff;
            mm = __int_as_float(k);
        }
        const float wa = ex2(la - mm), wb = ex2(lb - mm), we = ex2(le - mm);
        const float v0 = fmaf(we, __uint_as_float(e.x), fmaf(wb, __uint_as_float(b.x), wa * __uint_as_float(a.x)));
        const float v1 = fmaf(we, __uint_as_float(e.z), fmaf(wb, __uint_as_float(b.z), wa * __uint_as_float(a.z)));
        float ws = wa + wb + we;
        float kk = (lane & 8) ? v1 : v0;
        kk += __shfl_xor_sync(0xffffffffu, (lane & 8) ? v0 : v1, 8);
        ws += __shfl_xor_sync(0xffffffffu, ws, 8);
        if (!TAIL) {
            if (OPTA & 1) mbar_wait(SM_WBAR, 1);
#pragma unroll
            for (int mt = 0; mt < S1_NPRE; mt++) {
                ldsm4t(f0[mt], wa0 ^ (mt << 5));
                ldsm4t(f1[mt], (wa0 ^ (mt << 5)) + USTR);
            }
        }
#pragma unroll
        for (int k = 4; k > 0; k >>= 1) {
            kk += __shfl_xor_sync(0xffffffffu, kk, k);
            ws += __shfl_xor_sync(0xffffffffu, ws, k);
        }
        {
            float r; asm("rcp.approx.ftz.f32 %0, %1;" : "=f"(r) : "f"(ws));
            const uint32_t o = pack_bf16(kk * r, 0.f);
            if ((lane & 7) == 0) sts16(SM_RED + 128 + (wq & 3) * 16 + (wq >> 2) * 8 + ((lane >> 3) & 1) * 4 + (lane >> 4) * 2, o);
        }
        uint4* out = &g_s.ar[TAIL ? 2 : 0][cta & 1][wq * 16 + (lane >> 1)][lane & 1];
        __syncthreads();
        TS(TB + 1);
        const uint4 ob = lds128(SM_RED + 128 + t * 16);
        float c0[4] = {0.f, 0.f, 0.f, 0.f}, c1[4] = {0.f, 0.f, 0.f, 0.f};
#pragma unroll
        for (int mt = 0; mt < 4; mt++) {
            constexpr int NP = TAIL ? 4 : S1_NPRE;
            uint32_t* g0 = f0[mt % NP];
            uint32_t* g1 = f1[mt % NP];
            if (mt >= NP) {
                ldsm4t(g0, wa0 ^ (mt << 5));
                ldsm4t(g1, (wa0 ^ (mt << 5)) + USTR);
            }
            const bool mine = (g >> 1) == mt;
            mma(c0, g0, mine ? ob.x : 0u, mine ? ob.y : 0u);
            mma(c1, g1, mine ? ob.z : 0u, mine ? ob.w : 0u);
        }
        ar_add(out, c0[0] + c1[0], c0[2] + c1[2]);
        TS(TB + 2);
        if (!TAIL) {
            if (wq == 4 || wq == 5) bar_sync(4, 256); else bar_arrive(4, 256);
        }
    }
#pragma unroll 1
    for (int hv = 0; hv < 2; hv++) {
        const int half = __shfl_sync(0xffffffffu, hv, 0);
        const bool ffn = cta < 112;
        if (TAIL && (half ? cta != 0 : !ffn)) break;
        uint32_t t0;
        asm volatile("mov.u32 %0, %%clock;" : "=r"(t0));
        const int lane = tid_now() & 31, g = lane >> 2, t = lane & 3;
        const bool qs = !TAIL && half;
        [[maybe_unused]] const int h = wq - 4;
        [[maybe_unused]] const uint32_t z = SM_SLOTS + h * USTR;
        if (!TAIL && (wq == 4 || wq == 5)) {
            if (!half) {
                if (ffn) load_ffn(tm, cta, h, z);
            } else if (!(WQ_EARLY && ffn && h == 0)) {
                if (!ffn) delay_cycles(D_SKIP);
                load_wq(tm, cta, h, z);
            }
        }
        if (!TAIL && !half && wq >= 6) {
            delay_cycles(wq == 6 ? D_QP0 : D_QP1);
            l2_prefetch(p.wq + (size_t)(cta + (wq - 6) * 128) * 16384, 16384);
        }
        constexpr int NPRE = TAIL ? 4 : MID_NPRE;
        uint32_t f[NPRE][8];
        const int row = (wq & 3) * 64 + (lane & 7) + (lane >> 4) * 8;
        const uint32_t a0 = qs ? SM_SLOTS + (wq >> 2) * USTR + row * 64 + ((((lane >> 3) & 1) ^ ((lane >> 1) & 3)) << 4)
                               : SM_WG + (wq >> 2) * 8192 + row * 32 + ((((lane >> 3) ^ (lane >> 2)) & 1) << 4);
        const uint32_t a1 = qs ? a0 ^ 32 : a0 - (SM_WG - Z_GU), kstride = qs ? 1024 : 512;
        {
            const uint4* src = &g_s.ar[(TAIL ? 2 : 0) + half][0][wq * 16 + (lane >> 1)][lane & 1];
            const uint32_t cnt = __float_as_uint(half ? 56.f : 64.f);
            if (TAIL && !half) {
                mbar_wait(SM_WBAR, 0);
#pragma unroll
                for (int ks = 0; ks < NPRE; ks++) {
                    ldsm4t(f[ks], a0 + ks * kstride);
                    ldsm4t(f[ks] + 4, a1 + ks * kstride);
                }
            }
            {
                const uint32_t d = (half && !ffn) ? D_AR + D_SKIP : D_AR;
                uint32_t t1;
                do { asm volatile("mov.u32 %0, %%clock;" : "=r"(t1)); } while (t1 - t0 < d);
            }
            uint4 u, v;
            uint32_t it = 0;
            do {
                spin_guard(it);
                u = ll_ld(src);
                v = ll_ld(src + 1024);
            } while (__any_sync(0xffffffffu, u.x != cnt || u.w != cnt || v.x != cnt || v.w != cnt));
            const uint32_t y = pack_bf16(__uint_as_float(u.y) + __uint_as_float(v.y), __uint_as_float(u.z) + __uint_as_float(v.z));
            xo = pack_bf16(bf_lo(xo) + bf_lo(y), bf_hi(xo) + bf_hi(y));
        }
        if (half) TS(TB + 7); else TS(TB + 3);
        if (!half && !ffn) continue;
        const uint32_t xw = movm(xo);
        if (TAIL && half) {
            reinterpret_cast<uint32_t*>(p.out)[wq * 32 + lane] = xw;
            if (wq == 0) {
                if (lane < 16) g_s.ticket[lane >> 3][lane & 7][0] = 0;
                if (lane == 16) g_s.epoch = (tag >> 2) + 1;
            }
            break;
        }
        if (!TAIL) {
            mbar_wait(SM_WBAR, qs && ffn);
#pragma unroll
            for (int ks = 0; ks < NPRE; ks++) {
                ldsm4t(f[ks], a0 + ks * kstride);
                ldsm4t(f[ks] + 4, a1 + ks * kstride);
            }
        }
        if (half) TS(8); else TS(TB + 4);
        ln_gemv_part<NPRE>(f, a0, a1, kstride, xw, wq, lane);
        const uint32_t wd0 = Z_GU + USTR + wq * 2048 + ((lane & 7) + (lane >> 4) * 8) * 128 + ((((lane >> 3) & 1) ^ (lane & 7)) << 4);
        uint32_t d[4][4];
        constexpr int DPRE = TAIL ? 4 : MID_DPRE;
        if ((OPTA & 2) && !qs) mbar_wait(SM_DBAR + 8, TAIL);
#pragma unroll
        for (int mt = 0; mt < DPRE; mt++) ldsm4t(d[mt], wd0 ^ (mt << 5));
        uint4* out = qs ? q_dst(p, 1, cta, lane) : &g_s.ar[TAIL ? 3 : 1][cta & 1][wq * 16 + (lane >> 1)][lane & 1];
        __syncthreads();
        if (!half) TS(TB + 5);
        if (WQ_EARLY && !TAIL && !half && wq == 4) load_wq(tm, cta, 0, z);
        float r = ln_gemv_fin(lane);
        if (qs) {
            if (wq == 0) publish_q(out, r, tag, lane);
            if (cta == 0)
                asm volatile("st.relaxed.gpu.global.b64 [%0], %1;" ::"l"(&g_s.x2[wq * 32 + lane]), "l"((unsigned long long)tag << 32 | xo) : "memory");
            __syncthreads();
            TS(9);
            break;
        }
        r = bf16r(r);
        const float up = __shfl_down_sync(0xffffffffu, r, 16);
#pragma unroll
        for (int mt = DPRE; mt < 4; mt++) ldsm4t(d[mt], wd0 ^ (mt << 5));
        const float hh = (r > 0.f ? r : 0.f * r) * up;
        const float h0 = __shfl_sync(0xffffffffu, hh, 2 * t), h1 = __shfl_sync(0xffffffffu, hh, 2 * t + 1);
        const float h2 = __shfl_sync(0xffffffffu, hh, 2 * t + 8), h3 = __shfl_sync(0xffffffffu, hh, 2 * t + 9);
        const uint32_t b0 = pack_bf16(h0, h1), b1 = pack_bf16(h2, h3);
        float c0[4] = {0.f, 0.f, 0.f, 0.f}, c1[4] = {0.f, 0.f, 0.f, 0.f};
#pragma unroll
        for (int mt = 0; mt < 4; mt++) {
            const bool mine = (g >> 1) == mt;
            mma((mt & 1) ? c1 : c0, d[mt], mine ? b0 : 0u, mine ? b1 : 0u);
        }
        ar_add(out, c0[0] + c1[0], c0[2] + c1[2]);
        TS(TB + 6);
        if (!TAIL) {
            if (wq == 4 || wq == 5) bar_sync(4, 256); else bar_arrive(4, 256);
        }
    }
}

#define UVARS                                                                                               \
    const int wqu = __shfl_sync(0xffffffffu, tid_now() >> 5, 0);                                            \
    const int wg = wqu >> 2, wj = wqu & 3;                                                                  \
    [[maybe_unused]] const int head = unit_head(cta, wg), ui = unit_index(cta, wg), tb = head * NTILE;      \
    [[maybe_unused]] const uint32_t slots = SM_SLOTS + wg * USTR, bars = SM_BAR + wg * 48;                  \
    [[maybe_unused]] const int barid = 1 + wg;                                                              \
    [[maybe_unused]] const uint32_t qbase = cta < 128 ? SM_Q : SM_WG + wg * 1024;                           \
    [[maybe_unused]] const uint32_t rec = SM_ST + wg * 16;                                                  \
    [[maybe_unused]] const uint32_t mx = SM_MX + wg * 64;
#define Q_RD (qbase + (lane & 15) * 16)
#define P_RD (SM_P + wg * 512 + (lane & 15) * 16)
#define P_WR (SM_P + wg * 512 + (wj >> 1) * 256 + (wj & 1) * 8 + (lane & 15) * 16)

__device__ __forceinline__ void static_phase(const Maps& tm, const int cta, Acc& acc, uint32_t (*rp)[48]) {
    UVARS
#pragma unroll 1
    for (int rv = 0; rv < NSTAT; rv++) {
        const int rn = __shfl_sync(0xffffffffu, rv, 0);
        const int lane = tid_now() & 31;
        const uint32_t d = (uint32_t)(0x10210432105432ull >> (8 * rn)), par = 0x7c0u >> (2 * rn);
        const int sk = d & 7, sv = (d >> 4) & 7;
        Pack pk;
        pk.cmp = SM_CMP + wg * 16;
        pk.esc = SM_ESC + wg * (ECAP * 8);
        pk.key = (rn < 4 ? rn + 3 : 6 - rn) << 11 | wj << 5 | lane;
        const bool inplace = rn < 4;
        uint32_t dst = slots + 2 * SLOT + (6 - rn) * 24576 + (wj * 32 + lane) * 16;
        uint32_t kb = k_offset(slots, wj, lane) + sk * SLOT;
        float s[4] = {0.f, 0.f, 0.f, 0.f}, s2[4] = {0.f, 0.f, 0.f, 0.f};
        uint32_t a[16];
        mbar_wait(bars + sk * 8, par & 1);
        {
            const uint32_t b4 = lds32(pk.cmp);
#pragma unroll SUNR
            for (int hv = 0; hv < 2; hv++) {
                const int h = __shfl_sync(0xffffffffu, hv, 0);
                load_khalf(a, kb);
                pack16(a, b4, inplace ? kb : dst, inplace ? kb ^ 32 : dst + 2048, inplace ? kb ^ 64 : dst + 4096, h, pk);
                qk_half(s, s2, a, Q_RD + h * 512);
                kb += 8192; dst += 6144;
            }
        }
#pragma unroll
        for (int i = 0; i < 4; i++) s[i] += s2[i];
        softmax_step(s, acc, P_WR, mx, barid, lane, wj);
        if (EARLY_K && rn >= 5 && wj == 1) tma_tile(rn == 5 ? &tm.v : &tm.k, tb + (rn + 1) * NUNIT + ui, slots + sk * SLOT, bars + sk * 8);
        __syncwarp();
        uint32_t vb = v_offset(slots, wj, lane) + sv * SLOT;
        mbar_wait(bars + sv * 8, (par >> 1) & 1);
        {
            const uint32_t b4 = lds32(pk.cmp + 4);
#pragma unroll SUNR
            for (int yv = 0; yv < 2; yv++) {
                const int y = __shfl_sync(0xffffffffu, yv, 0);
                load_vhalf(a, vb);
                pack16(a, b4, inplace ? vb : dst, inplace ? vb ^ 32 : dst + 2048, inplace ? vb + 2048 : dst + 4096, 2 + y, pk);
                pv_half<true>(acc, a, SM_P + wg * 512 + (tid_now() & 15) * 16 + y * 256);
                vb += 4096; dst += 6144;
            }
            vb -= 8192;
        }
        {
            const uint32_t kb2 = k_offset(slots, wj, tid_now() & 31) + sk * SLOT;
            if (rn == 0) park(rp[0], kb2, vb);
            if (rn == 1) park(rp[1], kb2, vb);
            if (rn == 2) park(rp[2], kb2, vb);
            if (rn == 3) park(rp[3], kb2, vb);
        }
        asm volatile("fence.proxy.async.shared::cta;" ::: "memory");
        bar_sync(barid + 9, 128);
        const int j = (int)((wj == 1 ? (EARLY_K ? 0x00c0a86u : 0xe0c0a86u) : (EARLY_K ? 0xf00b907u : 0xfd0b907u)) >> (4 * rn)) & 15;
        if ((wj == 1 || wj == 2) && j) issue_item(j, tm, tb, ui, slots, bars);
        if (wj == 0) {
            const uint32_t st = lds32(rec + 4);
            if (lane == 0 && lds32(pk.cmp + 8) > ECAP) {
                sts16(SM_KEEP + wg * 64 + (st & 255) * 2, rn * NUNIT + ui);
                sts32(rec + 4, (st + 1) | 0x10000u << (pk.key >> 11));
            }
            __syncwarp();
        }
    }
    TSD(28);
    {
        uint32_t c = slots + 2 * SLOT + 12288 + (tid_now() & 127) * 16;
#pragma unroll 1
        for (int j = 0; j < 6; j++, c += 2048) {
            const uint4 u = lds128(c), v = lds128(c + 36864);
            sts128(c, v.x, v.y, v.z, v.w);
            sts128(c + 36864, u.x, u.y, u.z, u.w);
        }
        asm volatile("fence.proxy.async.shared::cta;" ::: "memory");
    }
    if (wqu == 0) __threadfence();
    bar_sync(barid + 9, 128);
}

__device__ __forceinline__ void acc_init(Acc& a) {
#pragma unroll
    for (int i = 0; i < 4; i++) { a.o[0][i] = 0.f; a.o[1][i] = 0.f; a.l[i] = 0.f; }
    a.m0 = a.m1 = __int_as_float(0xff800000);
}

__device__ __forceinline__ void attention_pass(const Maps& tm, const Params& p, const int cta, const int ph, const uint32_t tag0,
                                               Acc& acc, uint32_t (*rp)[48], float* s, const uint32_t allflags) {
    UVARS
    const int lim = ph ? T_KEEP0 : NTILE;
    uint32_t ticket = 0;
    if (wj == 0) draw_ticket(ticket, p, ph, head, tid_now() & 31);
    const uint32_t st0 = __shfl_sync(0xffffffffu, lds32(rec + 4), 0);
    uint32_t phbits = __shfl_sync(0xffffffffu, lds32(rec + 12), 0);
    int nk = st0 & 255;
    uint32_t cur = DESC(0, 1) | 256;
    uint32_t q0 = 0, q1 = 0;
    int rn = NSTAT, ki = 0, since = KRATIO;
    bool open = true;
    if (ph) {
        rn = 0; q0 = DESC(0, 3) | 256; cur = DESC(2, 1) | 128;
        if (nk > 0 && __shfl_sync(0xffffffffu, (int)lds16(SM_KEEP + wg * 64 + nk * 2 - 2), 0) >= T_KEEP0) nk--;
        else cur |= 512;
    }
#pragma unroll 1
    while (true) {
        const int lane = tid_now() & 31;
        const int sk = cur & 7, sv = (cur >> 3) & 7;
        const bool keeps = ph && ki < nk && cur;
        const bool want = cur && open && (!(q0 & 256) || (keeps && since < KRATIO));
        int tkeep = 0;
        if (keeps) tkeep = __shfl_sync(0xffffffffu, lds16(SM_KEEP + wg * 64 + ki * 2), 0);
        const bool resid = rn + (cur == 0) < NSTAT;
        if (cur ? !(cur & 512) : !(st0 >> (16 + rn) & 1)) {
            Pack pk;
            pk.cmp = SM_CMP + wg * 16;
            pk.esc = SM_ESC + wg * (ECAP * 8);
            pk.key = rn << 11 | wj << 5 | lane;
            uint32_t a[16], vb, flags = 0;
            if (cur) {
                vb = v_offset(slots, wj, lane) + sv * SLOT;
                if (!(cur & 128)) {
                    const uint32_t kb = k_offset(slots, wj, lane) + sk * SLOT;
                    float s2[4] = {0.f, 0.f, 0.f, 0.f};
                    s[0] = s[1] = s[2] = s[3] = 0.f;
                    mbar_wait(bars + sk * 8, (phbits >> sk) & 1);
                    if (DBG_U && ph == DBG_PH) TSW(26);
                    load_khalf(a, kb);
                    qk_half(s, s2, a, Q_RD);
                    load_khalf(a, kb + 8192);
                    qk_half(s, s2, a, Q_RD + 512);
                    mbar_wait(bars + sv * 8, (phbits >> sv) & 1);
                    phbits ^= 1u << sk | 1u << sv;
#pragma unroll
                    for (int i = 0; i < 4; i++) s[i] += s2[i];
                }
                load_vhalf(a, vb);
            } else {
                vb = slots + 2 * SLOT + (wj * 32 + lane) * 16;
                flags = allflags >> (4 * rn);
                if (rn < 3) {
                    const uint4 u = lds128(((vb & ~32u) | (rn & 1) << 5) + 32768 + (rn >> 1) * 2048);
                    s[0] = __uint_as_float(u.x); s[1] = __uint_as_float(u.y); s[2] = __uint_as_float(u.z); s[3] = __uint_as_float(u.w);
                    vb += ((0x423 >> (4 * rn)) & 7) * 12288;
                } else {
                    vb += 49152;
                    if (rn == 3) unpark(rp[0], vb);
                    if (rn == 4) unpark(rp[1], vb);
                    if (rn == 5) unpark(rp[2], vb);
                    if (rn == 6) unpark(rp[3], vb);
                    const uint32_t up = lds32(pk.cmp);
                    float s2[4] = {0.f, 0.f, 0.f, 0.f};
                    s[0] = s[1] = s[2] = s[3] = 0.f;
#pragma unroll 1
                    for (int h = 0; h < 2; h++) {
                        unpack16(a, up, vb + h * 6144, h, flags, pk);
                        qk_half(s, s2, a, Q_RD + h * 512);
                    }
#pragma unroll
                    for (int i = 0; i < 4; i++) s[i] += s2[i];
                }
                unpack16(a, lds32(pk.cmp + 4), vb + 12288, 2, flags, pk);
            }
            softmax_step(s, acc, P_WR, mx, barid, lane, wj);
            pv_half<false>(acc, a, P_RD);
            if (cur) load_vhalf(a, vb + 4096);
            else unpack16(a, lds32(pk.cmp + 4), vb + 18432, 3, flags, pk);
            pv_half<false>(acc, a, P_RD + 256);
        } else {
            bar_sync(barid + 9, 128);
        }
        if (wj == 0)
            asm volatile("{\n.reg .pred p, q;\n.reg .u32 w;\nmov.u32 w, %6;\nsetp.eq.u32 p, %7, 0;\n@p bra.uni N_%=;\n"
                         "shfl.sync.idx.b32 w, %1, 0, 31, 0xffffffff;\nadd.u32 w, w, %5;\nmin.u32 w, w, %6;\nN_%=:\n"
                         "setp.eq.u32 p, %2, 0;\nsetp.ge.and.u32 q, w, %3, p;\n@q or.b32 w, w, 0x10000;\n"
                         "@p st.shared.u32 [%0], w;\n@q red.relaxed.gpu.global.add.u32 [%4], 1;\n}"
                         ::"r"(rec), "r"(ticket), "r"(lane), "r"((!resid && !q0 && !keeps) ? lim : NTILE + 1),
                           "l"(&g_s.done[lane]), "n"(T_DYN0 + NUNIT), "n"(NTILE), "r"((uint32_t)want) : "memory");
        bar_sync(8 + wg, 128);
        int tv = __shfl_sync(0xffffffffu, (int)lds32(rec), 0);
        if (tv > NTILE) break;
        if (cur == 0) rn++;
        uint32_t push = 0;
        const bool streamed = tv < lim;
        if (streamed) push = (cur & 127) | 256;
        else if (keeps) { tv = tkeep; push = cur & 127; }
        if (push && (wj == 1 || wj == 2)) {
            const int sl = wj == 1 ? sk : sv;
            tma_tile(wj == 1 ? &tm.k : &tm.v, tb + tv, slots + sl * SLOT, bars + sl * 8);
            if (!ph && tv >= T_KEEP0 && tv < T_KEEPEND) l2_prefetch((wj == 1 ? p.k : p.v) + (size_t)(tb + tv) * SLOT, SLOT);
        }
        if (streamed) {
            since++;

            if (!ph && tv >= T_KEEP0) {
                if (wj == 3 && lane == 0) sts16(SM_KEEP + wg * 64 + nk * 2, tv);
                nk++;
                if (nk >= KEEPCAP) open = false;
            }
            if (open && wj == 0) draw_ticket(ticket, p, ph, head, lane);
        } else {
            if (want) open = false;
            if (keeps) { ki++; since = 0; }
        }
        if (q0) q1 |= push; else q0 = push;
        if (resid && (q0 == 0 || (streamed && q1 == 0))) {
            cur = 0;
        } else {
            cur = q0; q0 = q1; q1 = 0;
        }
    }
    const int lane = tid_now() & 31;
    {
        const int e = (lane >> 1) & 1;
        float l = e ? acc.l[1] : acc.l[0], m = e ? acc.m1 : acc.m0;
        float inv; asm("rcp.approx.ftz.f32 %0, %1;" : "=f"(inv) : "f"(l));
        float lg; asm("lg2.approx.ftz.f32 %0, %1;" : "=f"(lg) : "f"(l));
        uint32_t lam = __float_as_uint(m + lg);
        const uint32_t t16 = (tag0 + ph + 1) & 0xffffu;
        uint32_t ta = (lam & 0xffff0000u) | t16, tc = (lam << 16) | t16;
        uint4* dst = part_dst(p, head, ui, wqu * 32 + lane);
        ll_st(dst, __float_as_uint((e ? acc.o[0][1] : acc.o[0][0]) * inv), ta,
                   __float_as_uint((e ? acc.o[0][3] : acc.o[0][2]) * inv), tc);
        ll_st(dst + 4 * NUNIT * 2, __float_as_uint((e ? acc.o[1][1] : acc.o[1][0]) * inv), ta,
                                   __float_as_uint((e ? acc.o[1][3] : acc.o[1][2]) * inv), tc);
    }
    if (ph) TSW(38); else TSW(36);
    if (wj == 0 && lane == 0) {
        sts32(rec + 4, nk | (st0 & 0xffff0000u));
        sts32(rec + 12, phbits);
    }
}

__global__ void __launch_bounds__(256, 1)
fused_kernel(const __grid_constant__ Maps tm, const Params p) {
    extern __shared__ __align__(1024) unsigned char smem_raw[];
    const int cta = blockIdx.x;
    const bool worker = cta < 128;
    uint32_t tag0;
    if ((uint32_t)__cvta_generic_to_shared(smem_raw) != SM_BASE) __trap();
    TS(40);
    uint32_t rp[4][48];
    Acc acc;
    {
        UVARS
        const int lane = tid_now() & 31;
        if (wj == 1 && worker) l2_prefetch(p.wq + (size_t)(cta * 2 + wg) * SLOT, SLOT);
        if (wj == 0) {
#pragma unroll
            for (int i = 0; i < 6; i++) mbar_init(bars + i * 8, 1);
            mbar_init(SM_WBAR + wg * 8, 2);
            mbar_init(SM_DBAR + wg * 8, 1);
            asm volatile("fence.proxy.async.shared::cta;" ::: "memory");
            __syncwarp();
            if (worker && wg == 0) {
                load_wq(tm, cta, 0, SM_SLOTS + SLOT);
                load_wq(tm, cta, 1, SM_SLOTS + USTR + SLOT);
            }
            delay_cycles(D_KV);
            issue_item(0, tm, tb, ui, slots, bars);
            issue_item(1, tm, tb, ui, slots, bars);
        }
        if (wj == 1) {
            if (lane < ECAP) sts64(SM_ESC + wg * (ECAP * 8) + lane * 8, 0xffffffffu, 0);
            if (lane < 2) sts128(rec + lane * 32, 0, 0, 0, 0x27);
        }
        if (wj == 2) {
            const uint4 u = *reinterpret_cast<const uint4*>(p.x + wg * 256 + lane * 8);
            sts128(SM_P + wg * 512 + lane * 16, u.x, u.y, u.z, u.w);
        }
        if (wqu == 7 && worker && lane < 16) ll_st(&g_s.ar[0][0][0][0] + (cta * 8 + (lane >> 1)) * 8 + (lane & 1), 0, 0, 0, 0);
        if (wqu == 3) {
            uint32_t e;
            asm volatile("ld.relaxed.gpu.global.u32 %0, [%1];" : "=r"(e) : "l"(&g_s.epoch) : "memory");
            sts32(SM_RED, e * 4 + 1);
        }
        __syncthreads();
        tag0 = __shfl_sync(0xffffffffu, lds32(SM_RED), 0);
        const uint32_t xw = lds32(SM_P + wqu * 128 + lane * 4);
        __syncthreads();
        uint32_t it = 0;
        int item = 2;
#pragma unroll 1
        for (int stage = worker ? 0 : 1; stage < 3 || item < 6;) {
            if (item < (stage ? 6 : 5) && (wj != 1 || stage == 3 || mbar_test(bars + item * 8, 0))) {
                if (wj == 1) issue_item(item, tm, tb, ui, slots, bars);
                item++;
                continue;
            }
            spin_guard(it);
            if (stage == 0) {
                if (!mbar_test(SM_WBAR, 0)) continue;
                TS(32);
                const int row = wj * 64 + (lane & 7) + (lane >> 4) * 8;
                const uint32_t a0 = slots + SLOT + row * 64 + ((((lane >> 3) & 1) ^ ((lane >> 1) & 3)) << 4);
                uint32_t f[1][8];
                ldsm4t(f[0], a0);
                ldsm4t(f[0] + 4, a0 ^ 32);
                ln_gemv_part<1>(f, a0, a0 ^ 32, 1024, xw, wqu, lane);
                __syncthreads();
                if (wqu == 0) publish_q(q_dst(p, 0, cta, lane), ln_gemv_fin(lane), tag0, lane);
                if (wqu == 6 && cta < 112) {
                    expect_tx(SM_DBAR, SLOT);
                    tma_2d(&tm.wg, cta * 16, 0, SM_WG, SM_DBAR);
                    tma_2d(&tm.wg, cta * 16, 256, SM_WG + 8192, SM_DBAR);
                }
                __syncthreads();
                TS(33);
            } else if (stage == 1) {
                if (!mbar_test(bars + 2 * 8, 0) || !mbar_test(bars + 3 * 8, 0)) continue;
#pragma unroll 1
                for (int h = 0; h < 4; h++) {
                    uint32_t r[16], m = 0;
                    load_khalf(r, k_offset(slots, wj, lane) + 2 * SLOT + h * 8192);
#pragma unroll
                    for (int j = 0; j < 16; j++) m = __vmaxu2(m, r[j] & 0x7fff7fffu);
                    m = __reduce_max_sync(0xffffffffu, max(m >> 23, (m >> 7) & 0xffu));
                    if (lane == 0)
                        asm volatile("red.shared.max.u32 [%0], %1;" ::"r"(SM_CMP + wg * 16 + (h & 2) * 2),
                                     "r"((min(max(m, 15u), 141u) + 112u) * 0x00800080u) : "memory");
                    __syncwarp();
                }
            } else {
                const uint4 v = ll_ld(&g_s.q[0][cta >> 7][head][wj * 32 + lane]);
                if (__any_sync(0xffffffffu, v.y != tag0 || v.w != tag0)) { delay_cycles(200); continue; }
                sts64(qbase + (wj * 32 + lane) * 8, v.x, v.z);
            }
            stage++;
        }
        bar_sync(barid + 9, 128);
        TS(34);
#pragma unroll
        for (int i = 0; i < 4; i++)
#pragma unroll
            for (int j = 0; j < 48; j++) asm volatile("" : "=r"(rp[i][j]));
        acc_init(acc);
    }
    static_phase(tm, cta, acc, rp);
    float s[4] = {0.f, 0.f, 0.f, 0.f};
    uint32_t allflags = 0;
#pragma unroll 1
    for (int phv = 0;; phv = 1) {
        const int ph = __shfl_sync(0xffffffffu, phv, 0);
        attention_pass(tm, p, cta, ph, tag0, acc, rp, s, allflags);
        if (ph) break;
        uint32_t rx[32];
        {
            UVARS
            load_kfrag(rx, k_offset(slots, wj, tid_now() & 31));
            bar_sync(barid + 9, 128);
            if (worker && wj == 3) tma_rows(&tm.wo, cta * 32 + wg * 16, slots, SM_WBAR);
            if (cta < 112) mbar_wait(SM_DBAR, 0);
        }
        if (worker) gemv_chain<false>(tm, p, cta, tag0 + 1);
        UVARS
        const int lane = tid_now() & 31;
        const uint4* src = &g_s.q[1][cta >> 7][head][wj * 32 + lane];
        Pack pk = {SM_CMP + wg * 16, SM_ESC + wg * (ECAP * 8), (uint32_t)(wj << 5 | lane)};
        allflags = esc_flags(pk);
        uint4 v;
        uint32_t it = 0;
        do {
            spin_guard(it);
            if (it == 1 || !worker) delay_cycles(D_AG);
            v = ll_ld(src);
            if (it == 1 && wj == 1) tma_tile(&tm.k, tb + T_DYN0 + ui, slots, bars);
        } while (__any_sync(0xffffffffu, v.y != tag0 + 1 || v.w != tag0 + 1));
        sts64(qbase + (wj * 32 + lane) * 8, v.x, v.z);
        bar_sync(barid + 9, 128);
        TS(10);
        float s2[4] = {0.f, 0.f, 0.f, 0.f};
        s[0] = s[1] = s[2] = s[3] = 0.f;
        qk_half(s, s2, rx, Q_RD);
        qk_half(s, s2, rx + 16, Q_RD + 512);
#pragma unroll
        for (int i = 0; i < 4; i++) s[i] += s2[i];
        {
            const uint32_t store = slots + 2 * SLOT + (wj * 32 + lane) * 16, up = lds32(pk.cmp);
#pragma unroll 1
            for (int pv = 2; pv >= 0; pv--) {
                const int pos = __shfl_sync(0xffffffffu, pv, 0), c = (0x120 >> (4 * pos)) & 3;
                pk.key = c << 11 | wj << 5 | lane;
                float z[4] = {0.f, 0.f, 0.f, 0.f}, z2[4] = {0.f, 0.f, 0.f, 0.f};
#pragma unroll 1
                for (int h = 0; h < 2; h++) {
                    uint32_t a[16];
                    const uint4 q0 = lds128(Q_RD + h * 512), q1 = lds128(Q_RD + h * 512 + 256);
                    unpack16(a, up, store + pos * 12288 + h * 6144, h, allflags >> (4 * c), pk);
                    mma(z, a, q0.x, q0.y);
                    mma(z2, a + 4, q0.z, q0.w);
                    mma(z, a + 8, q1.x, q1.y);
                    mma(z2, a + 12, q1.z, q1.w);
                }
                asm volatile("{\n.reg .pred p;\nsetp.eq.u32 p, %5, 0;\n@p st.shared.v4.f32 [%0], {%1,%2,%3,%4};\n}"
                             ::"r"(store + 32768 + (c >> 1) * 2048), "f"(z[0] + z2[0]), "f"(z[1] + z2[1]), "f"(z[2] + z2[2]),
                               "f"(z[3] + z2[3]), "r"(((lane >> 1) ^ c) & 1) : "memory");
                if (pos == 1) {
                    bar_sync(8 + wg, 128);
                    if (wj == 2) tma_tile(&tm.v, tb + T_DYN0 + ui, slots + 3 * SLOT, bars + 24);
                    TS(13);
                }
                __syncwarp();
            }
        }
        acc_init(acc);
    }
    if (worker) {
        UVARS
        if (wj == 3) tma_rows(&tm.wo, cta * 32 + wg * 16, slots + 2 * SLOT, SM_TBAR);
        if (wj == 2 && cta < 112) load_ffn(tm, cta, wg, slots + 3 * SLOT);
        gemv_chain<true>(tm, p, cta, tag0 + 2);
    }
}

typedef CUresult (*EncodeFn)(CUtensorMap*, CUtensorMapDataType, cuuint32_t, void*, const cuuint64_t*, const cuuint64_t*,
                             const cuuint32_t*, const cuuint32_t*, CUtensorMapInterleave, CUtensorMapSwizzle,
                             CUtensorMapL2promotion, CUtensorMapFloatOOBfill);

void make_map(EncodeFn encode, CUtensorMap* m, void* base, int rank, const cuuint64_t* gd, const cuuint64_t* gs,
              const cuuint32_t* bx, CUtensorMapSwizzle sw) {
    const cuuint32_t es[3] = {1, 1, 1};
    encode(m, CU_TENSOR_MAP_DATA_TYPE_BFLOAT16, rank, base, gd, gs, bx, es, CU_TENSOR_MAP_INTERLEAVE_NONE, sw,
           CU_TENSOR_MAP_L2_PROMOTION_NONE, CU_TENSOR_MAP_FLOAT_OOB_FILL_NONE);
}

}

extern "C" void kernel_launch(void* const* d_in, const int* in_sizes, int n_in, void* d_out, int out_size) {
    (void)in_sizes; (void)n_in; (void)out_size;
    static EncodeFn encode = nullptr;
    static void* scratch = nullptr;
    if (!encode) {
        void* fn = nullptr;
        cudaDriverEntryPointQueryResult qr;
        cudaGetDriverEntryPoint("cuTensorMapEncodeTiled", &fn, cudaEnableDefault, &qr);
        encode = (EncodeFn)fn;
        cudaGetSymbolAddress(&scratch, g_scratch);
        cudaFuncSetAttribute(fused_kernel, cudaFuncAttributeMaxDynamicSharedMemorySize, SM_TOTAL);
    }
    Maps tm;
    {
        const cuuint64_t gd[3] = {64, 8ull * 65536ull, 2}, gs[2] = {256, 128};
        const cuuint32_t bx[3] = {64, 64, 2};
        make_map(encode, &tm.k, d_in[1], 3, gd, gs, bx, CU_TENSOR_MAP_SWIZZLE_128B);
        make_map(encode, &tm.v, d_in[2], 3, gd, gs, bx, CU_TENSOR_MAP_SWIZZLE_128B);
    }
    {
        const cuuint64_t gd[2] = {4096, 512}, gs[1] = {8192};
        const cuuint32_t bx[2] = {32, 256};
        make_map(encode, &tm.wq, d_in[3], 2, gd, gs, bx, CU_TENSOR_MAP_SWIZZLE_64B);
    }
    {
        const cuuint64_t gd[3] = {64, 4096, 8}, gs[2] = {1024, 128};
        const cuuint32_t bx[3] = {64, 16, 8};
        make_map(encode, &tm.wo, d_in[4], 3, gd, gs, bx, CU_TENSOR_MAP_SWIZZLE_128B);
        const cuuint64_t gd2[3] = {64, 1792, 8};
        make_map(encode, &tm.wd, d_in[8], 3, gd2, gs, bx, CU_TENSOR_MAP_SWIZZLE_128B);
    }
    {
        const cuuint64_t gd[2] = {1792, 512}, gs[1] = {3584};
        const cuuint32_t bx[2] = {16, 256};
        make_map(encode, &tm.wg, d_in[6], 2, gd, gs, bx, CU_TENSOR_MAP_SWIZZLE_32B);
        make_map(encode, &tm.wu, d_in[7], 2, gd, gs, bx, CU_TENSOR_MAP_SWIZZLE_32B);
    }
    Params p;
    p.x = (const __nv_bfloat16*)d_in[0];
    p.k = (const char*)d_in[1];
    p.v = (const char*)d_in[2];
    p.wq = (const char*)d_in[3];
    p.wo = (const char*)d_in[4];
    p.wg = (const char*)d_in[6];
    p.wu = (const char*)d_in[7];
    p.wd = (const char*)d_in[8];
    p.out = (__nv_bfloat16*)d_out;
    p.s = (Scratch*)scratch;
    fused_kernel<<<NCTA, 256, SM_TOTAL, cudaStreamPerThread>>>(tm, p);
}
```
